```python
import torch

def _softmax(x, axis=-1):
    return torch.softmax(x, dim=axis)
def _gelu(x):
    return torch.nn.functional.gelu(x, approximate="tanh")
def _silu(x):
    return torch.nn.functional.silu(x)
def _sigmoid(x):
    return torch.sigmoid(x)
def _layernorm(x, axis=-1, eps=1e-5):
    m = x.mean(dim=axis, keepdim=True)
    v = x.var(dim=axis, keepdim=True, unbiased=False)
    return (x - m) / torch.sqrt(v + eps)
def _scatter_add(tgt, idx, src, axis=0):
    return tgt.clone().index_add_(axis, idx, src)
def _segment_sum(src, seg, n):
    out = torch.zeros((n,) + src.shape[1:], dtype=src.dtype)
    return out.index_add_(0, seg, src)
def _pad(x, pw):
    flat = tuple(v for pair in reversed(pw) for v in pair)
    return torch.nn.functional.pad(x, flat)

kernel_name = 'parallel_sum__mha_block__dense_activation_relu__prompt'

def setup_inputs():

    _w = (lambda a: (lambda t: t.to(torch.bfloat16) if t.is_floating_point() else t)(torch.as_tensor(a)))
    def _A_setup():
        B, S, D, H = 1, 2048, 1024, 32
        return {
            "x": _w((lambda *s: torch.randn(*s, dtype=torch.bfloat16) * 0.05)(B, S, D)),
            "wqkv": _w((lambda *s: torch.randn(*s, dtype=torch.bfloat16) * 0.05)(D, 3 * D)),
            "wo": _w((lambda *s: torch.randn(*s, dtype=torch.bfloat16) * 0.05)(D, D)),
        }
    _A_in = _A_setup()

    def _B_setup():
        B, S, D, Dff = 1, 2048, 1024, 3584
        return {
            "x": _w((lambda *s: torch.randn(*s, dtype=torch.bfloat16) * 0.05)(B, S, D)),
            "w1": _w((lambda *s: torch.randn(*s, dtype=torch.bfloat16) * 0.05)(D, Dff)),
            "w2": _w((lambda *s: torch.randn(*s, dtype=torch.bfloat16) * 0.05)(Dff, D)),
        }
    _B_in = _B_setup()

    return {
        "A_x": _A_in["x"],
        "A_wqkv": _A_in["wqkv"],
        "A_wo": _A_in["wo"],
        "B_x": _B_in["x"],
        "B_w1": _B_in["w1"],
        "B_w2": _B_in["w2"],
    }

def reference(A_x, A_wqkv, A_wo, B_x, B_w1, B_w2):
    def _A_ref(x, wqkv, wo):
        B, S, D = x.shape
        H = 32
        Dh = D // H
        qkv = (lambda x, *d: x.permute(*d))((x @ wqkv).reshape(B, S, 3, H, Dh), 2, 0, 3, 1, 4)
        q, k, v = qkv[0], qkv[1], qkv[2]
        scores = torch.einsum("bhqd,bhkd->bhqk", q, k) * (Dh ** -0.5)
        p = _softmax(scores, axis=-1)
        o = torch.einsum("bhqk,bhkd->bhqd", p, v)
        return (lambda x, *d: x.permute(*d))(o, 0, 2, 1, 3).reshape(B, S, D) @ wo

    def _B_ref(x, w1, w2):
        h = torch.einsum("bsd,df->bsf", x, w1)
        zero = torch.zeros_like(h)
        h = torch.maximum(h, zero)
        return torch.einsum("bsf,fd->bsd", h, w2)

    x = A_x
    xn = _layernorm(x, axis=-1)
    return x + _A_ref(xn, A_wqkv, A_wo) + _B_ref(xn, B_w1, B_w2)
```

```cpp
#include <cuda_runtime.h>
#include <cuda_bf16.h>
#include <cuda.h>
#include <stdint.h>

namespace {

#define PF 0
#define CHUNK 2048
#define PACE 300
#define PFX 99
#define XPOS 2
#define XPACE 60
constexpr int NCTA = 128;
#define D1V 5
constexpr int D1 = D1V;
constexpr int NATT_FINAL = 129 - (2 * (16 - D1) + 32 + 16);

constexpr uint32_t OFF_KV = 196608;
constexpr uint32_t OFF_QO = OFF_KV + 24576;
constexpr uint32_t OFF_BAR = OFF_QO + 8192;
constexpr uint32_t B_FULL48 = OFF_BAR, B_EMPTY48 = B_FULL48 + 32, B_FULL32 = B_EMPTY48 + 32, B_EMPTY32 = B_FULL32 + 48,
                   B_KVFULL = B_EMPTY32 + 48, B_KVEMPTY = B_KVFULL + 24, B_STAGED = B_KVEMPTY + 24,
                   B_OFREE = B_STAGED + 192,
                   B_LNRDY = B_OFREE + 24,
                   B_STGFREE = B_LNRDY + 8;
constexpr uint32_t B_XNDONE = B_STGFREE + 24;
constexpr uint32_t OFF_SAFE = OFF_BAR + 480;
constexpr uint32_t OFF_NRM = OFF_BAR + 512;
constexpr uint32_t OFF_ONES = OFF_BAR + 1024;
constexpr uint32_t OFF_CS = OFF_ONES + 1024;
constexpr uint32_t SMEM_BYTES = OFF_CS + 1024;
enum { EV_T1, EV_T2, EV_T3, EV_T4, EV_FIN, EV_LN, EV_CS, EV_O0 };

struct Sync {
  unsigned ln[16 * 8], st[16 * 8], cs[8 * 8];
  unsigned qkv[24 * 8];
  unsigned hA[16 * 8], hB[16 * 8], hC[16 * 8];
  unsigned oc[64 * 8];
  unsigned done[32];
};

__device__ __align__(1024) uint8_t g_xn[16 * 16 * 16384];
__device__ __align__(1024) uint8_t g_h[16 * 56 * 16384];
__device__ __align__(1024) uint8_t g_q[32 * 32 * 4096];
__device__ __align__(1024) uint8_t g_k[32 * 32 * 4096];
__device__ __align__(1024) uint8_t g_v[32 * 32 * 4096];
__device__ __align__(1024) __nv_bfloat16 g_o[2048 * 1024];
__device__ __align__(1024) uint4 g_nrm[16 * 32 * 8];
__device__ __align__(1024) float2 g_stat[2048];
__device__ __align__(1024) float g_csp[8 * 8 * 192];
__device__ __align__(1024) Sync g_sync;

#define MARK(i)
#define MARKS(i)
#define MARKP(i)

__device__ __forceinline__ void mbar_init(uint32_t b, uint32_t c) { asm volatile("mbarrier.init.shared::cta.b64 [%0], %1;" ::"r"(b), "r"(c) : "memory"); }
__device__ __forceinline__ void mbar_expect(uint32_t b, uint32_t bytes) { asm volatile("mbarrier.arrive.expect_tx.shared::cta.b64 _, [%0], %1;" ::"r"(b), "r"(bytes) : "memory"); }
__device__ __forceinline__ void mbar_arrive(uint32_t b) { asm volatile("mbarrier.arrive.shared::cta.b64 _, [%0];" ::"r"(b) : "memory"); }
__device__ __forceinline__ void mbar_arrive_cta(uint32_t b, uint32_t cta) {
  asm volatile("{\n.reg .b32 ra;\nmapa.shared::cluster.u32 ra, %0, %1;\nmbarrier.arrive.shared::cluster.b64 _, [ra];\n}" ::"r"(b), "r"(cta) : "memory");
}
__device__ __forceinline__ void mbar_arrive_remote(uint32_t cluster_addr) {
  asm volatile("mbarrier.arrive.shared::cluster.b64 _, [%0];" ::"r"(cluster_addr) : "memory");
}
__device__ __forceinline__ uint32_t mapa(uint32_t a, uint32_t cta) {
  uint32_t r; asm("mapa.shared::cluster.u32 %0, %1, %2;" : "=r"(r) : "r"(a), "r"(cta)); return r;
}
__device__ __forceinline__ bool elect_one() {
  uint32_t r;
  asm volatile("{\n.reg .pred p;\nelect.sync _|p, 0xffffffff;\nselp.u32 %0, 1, 0, p;\n}" : "=r"(r));
  return r != 0;
}
__device__ __forceinline__ void mbar_wait(uint32_t b, uint32_t ph) {
  asm volatile("{\n.reg .pred p;\n.reg .u32 n;\n"
               "mbarrier.try_wait.parity.shared::cta.b64 p, [%0], %1;\n@p bra LAB_DONE;\nmov.u32 n, 0;\n"
               "LAB_WAIT:\nmbarrier.try_wait.parity.shared::cta.b64 p, [%0], %1;\n@p bra LAB_DONE;\n"
               "add.u32 n, n, 1;\nsetp.lt.u32 p, n, 100000;\n@p bra LAB_WAIT;\ntrap;\nLAB_DONE:\n}" ::"r"(b), "r"(ph) : "memory");
}
__device__ __forceinline__ uint32_t mbar_test(uint32_t b, uint32_t ph) {
  uint32_t ok;
  asm volatile("{\n.reg .pred p;\nmbarrier.test_wait.parity.shared::cta.b64 p, [%1], %2;\nselp.u32 %0, 1, 0, p;\n}" : "=r"(ok) : "r"(b), "r"(ph) : "memory");
  return ok;
}
__device__ __forceinline__ void poll_ge(const unsigned* p, unsigned target) {
  asm volatile("{\n.reg .pred p;\n.reg .u32 n, v;\nmov.u32 n, 0;\n"
               "LAB_POLL:\nld.acquire.gpu.global.u32 v, [%0];\nsetp.ge.u32 p, v, %1;\n@p bra LAB_DONE;\n"
               "nanosleep.u32 40;\nadd.u32 n, n, 1;\nsetp.lt.u32 p, n, 1000000;\n@p bra LAB_POLL;\ntrap;\nLAB_DONE:\n"
               "fence.proxy.async.global;\n}" ::"l"(p), "r"(target) : "memory");
}
__device__ __forceinline__ unsigned peek(const unsigned* p) {
  unsigned v;
  asm volatile("ld.relaxed.gpu.global.u32 %0, [%1];" : "=r"(v) : "l"(p) : "memory");
  return v;
}
__device__ __forceinline__ void confirm(const unsigned* p, unsigned seen, unsigned target) {
  if (seen < target) poll_ge(p, target);
  else asm volatile("fence.proxy.async.global;" ::: "memory");
}
__device__ __forceinline__ void signal_release(unsigned* p) { asm volatile("red.release.gpu.global.add.u32 [%0], 1;" ::"l"(p) : "memory"); }
__device__ __forceinline__ void signal_relaxed(unsigned* p) { asm volatile("red.relaxed.gpu.global.add.u32 [%0], 1;" ::"l"(p) : "memory"); }
__device__ __forceinline__ void fence_async_smem() { asm volatile("fence.proxy.async.shared::cta;" ::: "memory"); }
constexpr uint64_t POL = 0x1000000000000000ull;
__device__ __forceinline__ void tma2d(uint32_t dst, const CUtensorMap* m, int c0, int c1, uint32_t bar) {
  asm volatile("cp.async.bulk.tensor.2d.shared::cluster.global.mbarrier::complete_tx::bytes.L2::cache_hint [%0], [%1, {%3, %4}], [%2], %5;"
               ::"r"(dst), "l"(m), "r"(bar), "r"(c0), "r"(c1), "l"(POL) : "memory");
}
__device__ __forceinline__ void tma2d_mc(uint32_t dst, const CUtensorMap* m, int c0, int c1, uint32_t bar) {
  asm volatile("cp.async.bulk.tensor.2d.shared::cluster.global.mbarrier::complete_tx::bytes.multicast::cluster.L2::cache_hint [%0], [%1, {%3, %4}], [%2], %5, %6;"
               ::"r"(dst), "l"(m), "r"(bar), "r"(c0), "r"(c1), "h"((uint16_t)3), "l"(POL) : "memory");
}
__device__ __forceinline__ void bulk_ld(uint32_t dst, const void* src, uint32_t bytes, uint32_t bar) {
  asm volatile("cp.async.bulk.shared::cluster.global.mbarrier::complete_tx::bytes [%0], [%1], %2, [%3];" ::"r"(dst), "l"(src), "r"(bytes), "r"(bar) : "memory");
}
__device__ __forceinline__ void bulk_ld_mc(uint32_t dst, const void* src, uint32_t bytes, uint32_t bar) {
  asm volatile("cp.async.bulk.shared::cluster.global.mbarrier::complete_tx::bytes.multicast::cluster [%0], [%1], %2, [%3], %4;"
               ::"r"(dst), "l"(src), "r"(bytes), "r"(bar), "h"((uint16_t)3) : "memory");
}
__device__ __forceinline__ void bulk_prefetch(const void* src, uint32_t bytes) {
  asm volatile("cp.async.bulk.prefetch.L2.global [%0], %1;" ::"l"(src), "r"(bytes) : "memory");
}
__device__ __forceinline__ void tma2d_pf(const CUtensorMap* m, int c0, int c1) {
  asm volatile("cp.async.bulk.prefetch.tensor.2d.L2.global [%0, {%1, %2}];" ::"l"(m), "r"(c0), "r"(c1) : "memory");
}
__device__ __forceinline__ void bulk_st(void* dst, uint32_t src, uint32_t bytes) {
  asm volatile("cp.async.bulk.global.shared::cta.bulk_group [%0], [%1], %2;" ::"l"(dst), "r"(src), "r"(bytes) : "memory");
}
__device__ __forceinline__ void tma2d_st(const CUtensorMap* m, int c0, int c1, uint32_t src) {
  asm volatile("cp.async.bulk.tensor.2d.global.shared::cta.bulk_group [%0, {%2, %3}], [%1];" ::"l"(m), "r"(src), "r"(c0), "r"(c1) : "memory");
}
__device__ __forceinline__ void bulk_commit() { asm volatile("cp.async.bulk.commit_group;" ::: "memory"); }
template <int N> __device__ __forceinline__ void bulk_wait_read() { asm volatile("cp.async.bulk.wait_group.read %0;" ::"n"(N) : "memory"); }
template <int N> __device__ __forceinline__ void bulk_wait() { asm volatile("cp.async.bulk.wait_group %0;" ::"n"(N) : "memory"); }
__device__ __forceinline__ void wg_fence() { asm volatile("wgmma.fence.sync.aligned;" ::: "memory"); }
__device__ __forceinline__ void wg_commit() { asm volatile("wgmma.commit_group.sync.aligned;" ::: "memory"); }
template <int N> __device__ __forceinline__ void wg_wait() { asm volatile("wgmma.wait_group.sync.aligned %0;" ::"n"(N) : "memory"); }
__device__ __forceinline__ float ex2(float x) { float y; asm("ex2.approx.ftz.f32 %0, %1;" : "=f"(y) : "f"(x)); return y; }
__device__ __forceinline__ float rcp(float x) { float y; asm("rcp.approx.ftz.f32 %0, %1;" : "=f"(y) : "f"(x)); return y; }
__device__ __forceinline__ uint32_t pack2(float lo, float hi) { uint32_t r; asm("cvt.rn.bf16x2.f32 %0, %1, %2;" : "=r"(r) : "f"(hi), "f"(lo)); return r; }
__device__ __forceinline__ uint32_t pack2_relu(float lo, float hi) { uint32_t r; asm("cvt.rn.relu.bf16x2.f32 %0, %1, %2;" : "=r"(r) : "f"(hi), "f"(lo)); return r; }
__device__ __forceinline__ float bf_lo(uint32_t u) { return __uint_as_float(u << 16); }
__device__ __forceinline__ float bf_hi(uint32_t u) { return __uint_as_float(u & 0xffff0000u); }
__device__ __forceinline__ float bf_round(float x) { return __bfloat162float(__float2bfloat16_rn(x)); }
__device__ __forceinline__ void stsm4(uint32_t a, uint32_t r0, uint32_t r1, uint32_t r2, uint32_t r3) {
  asm volatile("stmatrix.sync.aligned.m8n8.x4.shared.b16 [%0], {%1, %2, %3, %4};" ::"r"(a), "r"(r0), "r"(r1), "r"(r2), "r"(r3) : "memory");
}
__device__ __forceinline__ void ldsm4(uint32_t a, uint32_t& r0, uint32_t& r1, uint32_t& r2, uint32_t& r3) {
  asm volatile("ldmatrix.sync.aligned.m8n8.x4.shared.b16 {%0, %1, %2, %3}, [%4];" : "=r"(r0), "=r"(r1), "=r"(r2), "=r"(r3) : "r"(a) : "memory");
}
__device__ __forceinline__ void sts128(uint32_t a, uint32_t r0, uint32_t r1, uint32_t r2, uint32_t r3) {
  asm volatile("st.shared.v4.b32 [%0], {%1, %2, %3, %4};" ::"r"(a), "r"(r0), "r"(r1), "r"(r2), "r"(r3) : "memory");
}
__device__ __forceinline__ void lds128(uint32_t a, uint32_t& r0, uint32_t& r1, uint32_t& r2, uint32_t& r3) {
  asm volatile("ld.shared.v4.b32 {%0, %1, %2, %3}, [%4];" : "=r"(r0), "=r"(r1), "=r"(r2), "=r"(r3) : "r"(a) : "memory");
}
__device__ __forceinline__ void sts32(uint32_t a, uint32_t v) { asm volatile("st.shared.b32 [%0], %1;" ::"r"(a), "r"(v) : "memory"); }
__device__ __forceinline__ uint32_t lds32(uint32_t a) { uint32_t v; asm volatile("ld.shared.b32 %0, [%1];" : "=r"(v) : "r"(a) : "memory"); return v; }
template <int N> __device__ __forceinline__ void pin_f(float (&r)[N]) {
#pragma unroll
  for (int i = 0; i < N; i++) asm volatile("" : "+f"(r[i])::"memory");
}
template <int N> __device__ __forceinline__ void pin_u(uint32_t (&r)[N]) {
#pragma unroll
  for (int i = 0; i < N; i++) asm volatile("" : "+r"(r[i])::"memory");
}
template <int LO, int HI> __device__ __forceinline__ void pin_acc(float (&r)[128]) {
#pragma unroll
  for (int i = LO; i < HI; i++) asm volatile("" : "+f"(r[i])::"memory");
}

__device__ __forceinline__ void mma_ss_n128(float (&d)[128], uint32_t alo, uint32_t blo, uint32_t sd) {
  asm volatile("{\n.reg .pred p;\n.reg .b64 da, db;\nsetp.ne.b32 p, %66, 0;\n"
    "mov.b64 da, {%64, 0x40000040};\nmov.b64 db, {%65, 0x40000040};\n"
    "wgmma.mma_async.sync.aligned.m64n128k16.f32.bf16.bf16 {%0, %1, %2, %3, %4, %5, %6, %7, %8, %9, %10, %11, %12, %13, %14, %15, %16, %17, %18, %19, %20, %21, %22, %23, %24, %25, %26, %27, %28, %29, %30, %31, %32, %33, %34, %35, %36, %37, %38, %39, %40, %41, %42, %43, %44, %45, %46, %47, %48, %49, %50, %51, %52, %53, %54, %55, %56, %57, %58, %59, %60, %61, %62, %63}, da, db, p, 1, 1, 0, 1;\n}\n"
    : "+f"(d[0]), "+f"(d[1]), "+f"(d[2]), "+f"(d[3]), "+f"(d[4]), "+f"(d[5]), "+f"(d[6]), "+f"(d[7]), "+f"(d[8]), "+f"(d[9]), "+f"(d[10]), "+f"(d[11]), "+f"(d[12]), "+f"(d[13]), "+f"(d[14]), "+f"(d[15]), "+f"(d[16]), "+f"(d[17]), "+f"(d[18]), "+f"(d[19]), "+f"(d[20]), "+f"(d[21]), "+f"(d[22]), "+f"(d[23]), "+f"(d[24]), "+f"(d[25]), "+f"(d[26]), "+f"(d[27]), "+f"(d[28]), "+f"(d[29]), "+f"(d[30]), "+f"(d[31]), "+f"(d[32]), "+f"(d[33]), "+f"(d[34]), "+f"(d[35]), "+f"(d[36]), "+f"(d[37]), "+f"(d[38]), "+f"(d[39]), "+f"(d[40]), "+f"(d[41]), "+f"(d[42]), "+f"(d[43]), "+f"(d[44]), "+f"(d[45]), "+f"(d[46]), "+f"(d[47]), "+f"(d[48]), "+f"(d[49]), "+f"(d[50]), "+f"(d[51]), "+f"(d[52]), "+f"(d[53]), "+f"(d[54]), "+f"(d[55]), "+f"(d[56]), "+f"(d[57]), "+f"(d[58]), "+f"(d[59]), "+f"(d[60]), "+f"(d[61]), "+f"(d[62]), "+f"(d[63])
    : "r"(alo), "r"(blo), "r"(sd));
}
__device__ __forceinline__ void mma_ss_n192(float (&d)[128], uint32_t alo, uint32_t blo, uint32_t sd) {
  asm volatile("{\n.reg .pred p;\n.reg .b64 da, db;\nsetp.ne.b32 p, %98, 0;\n"
    "mov.b64 da, {%96, 0x40000040};\nmov.b64 db, {%97, 0x40000040};\n"
    "wgmma.mma_async.sync.aligned.m64n192k16.f32.bf16.bf16 {%0, %1, %2, %3, %4, %5, %6, %7, %8, %9, %10, %11, %12, %13, %14, %15, %16, %17, %18, %19, %20, %21, %22, %23, %24, %25, %26, %27, %28, %29, %30, %31, %32, %33, %34, %35, %36, %37, %38, %39, %40, %41, %42, %43, %44, %45, %46, %47, %48, %49, %50, %51, %52, %53, %54, %55, %56, %57, %58, %59, %60, %61, %62, %63, %64, %65, %66, %67, %68, %69, %70, %71, %72, %73, %74, %75, %76, %77, %78, %79, %80, %81, %82, %83, %84, %85, %86, %87, %88, %89, %90, %91, %92, %93, %94, %95}, da, db, p, 1, 1, 0, 1;\n}\n"
    : "+f"(d[0]), "+f"(d[1]), "+f"(d[2]), "+f"(d[3]), "+f"(d[4]), "+f"(d[5]), "+f"(d[6]), "+f"(d[7]), "+f"(d[8]), "+f"(d[9]), "+f"(d[10]), "+f"(d[11]), "+f"(d[12]), "+f"(d[13]), "+f"(d[14]), "+f"(d[15]), "+f"(d[16]), "+f"(d[17]), "+f"(d[18]), "+f"(d[19]), "+f"(d[20]), "+f"(d[21]), "+f"(d[22]), "+f"(d[23]), "+f"(d[24]), "+f"(d[25]), "+f"(d[26]), "+f"(d[27]), "+f"(d[28]), "+f"(d[29]), "+f"(d[30]), "+f"(d[31]), "+f"(d[32]), "+f"(d[33]), "+f"(d[34]), "+f"(d[35]), "+f"(d[36]), "+f"(d[37]), "+f"(d[38]), "+f"(d[39]), "+f"(d[40]), "+f"(d[41]), "+f"(d[42]), "+f"(d[43]), "+f"(d[44]), "+f"(d[45]), "+f"(d[46]), "+f"(d[47]), "+f"(d[48]), "+f"(d[49]), "+f"(d[50]), "+f"(d[51]), "+f"(d[52]), "+f"(d[53]), "+f"(d[54]), "+f"(d[55]), "+f"(d[56]), "+f"(d[57]), "+f"(d[58]), "+f"(d[59]), "+f"(d[60]), "+f"(d[61]), "+f"(d[62]), "+f"(d[63]), "+f"(d[64]), "+f"(d[65]), "+f"(d[66]), "+f"(d[67]), "+f"(d[68]), "+f"(d[69]), "+f"(d[70]), "+f"(d[71]), "+f"(d[72]), "+f"(d[73]), "+f"(d[74]), "+f"(d[75]), "+f"(d[76]), "+f"(d[77]), "+f"(d[78]), "+f"(d[79]), "+f"(d[80]), "+f"(d[81]), "+f"(d[82]), "+f"(d[83]), "+f"(d[84]), "+f"(d[85]), "+f"(d[86]), "+f"(d[87]), "+f"(d[88]), "+f"(d[89]), "+f"(d[90]), "+f"(d[91]), "+f"(d[92]), "+f"(d[93]), "+f"(d[94]), "+f"(d[95])
    : "r"(alo), "r"(blo), "r"(sd));
}
__device__ __forceinline__ void mma_ss_n256(float (&d)[128], uint32_t alo, uint32_t blo, uint32_t sd) {
  asm volatile("{\n.reg .pred p;\n.reg .b64 da, db;\nsetp.ne.b32 p, %130, 0;\n"
    "mov.b64 da, {%128, 0x40000040};\nmov.b64 db, {%129, 0x40000040};\n"
    "wgmma.mma_async.sync.aligned.m64n256k16.f32.bf16.bf16 {%0, %1, %2, %3, %4, %5, %6, %7, %8, %9, %10, %11, %12, %13, %14, %15, %16, %17, %18, %19, %20, %21, %22, %23, %24, %25, %26, %27, %28, %29, %30, %31, %32, %33, %34, %35, %36, %37, %38, %39, %40, %41, %42, %43, %44, %45, %46, %47, %48, %49, %50, %51, %52, %53, %54, %55, %56, %57, %58, %59, %60, %61, %62, %63, %64, %65, %66, %67, %68, %69, %70, %71, %72, %73, %74, %75, %76, %77, %78, %79, %80, %81, %82, %83, %84, %85, %86, %87, %88, %89, %90, %91, %92, %93, %94, %95, %96, %97, %98, %99, %100, %101, %102, %103, %104, %105, %106, %107, %108, %109, %110, %111, %112, %113, %114, %115, %116, %117, %118, %119, %120, %121, %122, %123, %124, %125, %126, %127}, da, db, p, 1, 1, 0, 1;\n}\n"
    : "+f"(d[0]), "+f"(d[1]), "+f"(d[2]), "+f"(d[3]), "+f"(d[4]), "+f"(d[5]), "+f"(d[6]), "+f"(d[7]), "+f"(d[8]), "+f"(d[9]), "+f"(d[10]), "+f"(d[11]), "+f"(d[12]), "+f"(d[13]), "+f"(d[14]), "+f"(d[15]), "+f"(d[16]), "+f"(d[17]), "+f"(d[18]), "+f"(d[19]), "+f"(d[20]), "+f"(d[21]), "+f"(d[22]), "+f"(d[23]), "+f"(d[24]), "+f"(d[25]), "+f"(d[26]), "+f"(d[27]), "+f"(d[28]), "+f"(d[29]), "+f"(d[30]), "+f"(d[31]), "+f"(d[32]), "+f"(d[33]), "+f"(d[34]), "+f"(d[35]), "+f"(d[36]), "+f"(d[37]), "+f"(d[38]), "+f"(d[39]), "+f"(d[40]), "+f"(d[41]), "+f"(d[42]), "+f"(d[43]), "+f"(d[44]), "+f"(d[45]), "+f"(d[46]), "+f"(d[47]), "+f"(d[48]), "+f"(d[49]), "+f"(d[50]), "+f"(d[51]), "+f"(d[52]), "+f"(d[53]), "+f"(d[54]), "+f"(d[55]), "+f"(d[56]), "+f"(d[57]), "+f"(d[58]), "+f"(d[59]), "+f"(d[60]), "+f"(d[61]), "+f"(d[62]), "+f"(d[63]), "+f"(d[64]), "+f"(d[65]), "+f"(d[66]), "+f"(d[67]), "+f"(d[68]), "+f"(d[69]), "+f"(d[70]), "+f"(d[71]), "+f"(d[72]), "+f"(d[73]), "+f"(d[74]), "+f"(d[75]), "+f"(d[76]), "+f"(d[77]), "+f"(d[78]), "+f"(d[79]), "+f"(d[80]), "+f"(d[81]), "+f"(d[82]), "+f"(d[83]), "+f"(d[84]), "+f"(d[85]), "+f"(d[86]), "+f"(d[87]), "+f"(d[88]), "+f"(d[89]), "+f"(d[90]), "+f"(d[91]), "+f"(d[92]), "+f"(d[93]), "+f"(d[94]), "+f"(d[95]), "+f"(d[96]), "+f"(d[97]), "+f"(d[98]), "+f"(d[99]), "+f"(d[100]), "+f"(d[101]), "+f"(d[102]), "+f"(d[103]), "+f"(d[104]), "+f"(d[105]), "+f"(d[106]), "+f"(d[107]), "+f"(d[108]), "+f"(d[109]), "+f"(d[110]), "+f"(d[111]), "+f"(d[112]), "+f"(d[113]), "+f"(d[114]), "+f"(d[115]), "+f"(d[116]), "+f"(d[117]), "+f"(d[118]), "+f"(d[119]), "+f"(d[120]), "+f"(d[121]), "+f"(d[122]), "+f"(d[123]), "+f"(d[124]), "+f"(d[125]), "+f"(d[126]), "+f"(d[127])
    : "r"(alo), "r"(blo), "r"(sd));
}
__device__ __forceinline__ void mma_qk(float (&d)[32], uint32_t a0, uint32_t a1, uint32_t a2, uint32_t a3, uint32_t blo, uint32_t sd) {
  asm volatile("{\n.reg .pred p;\n.reg .b64 db;\nsetp.ne.b32 p, %37, 0;\nmov.b64 db, {%36, 0x80000020};\n"
    "wgmma.mma_async.sync.aligned.m64n64k16.f32.bf16.bf16 {%0, %1, %2, %3, %4, %5, %6, %7, %8, %9, %10, %11, %12, %13, %14, %15, %16, %17, %18, %19, %20, %21, %22, %23, %24, %25, %26, %27, %28, %29, %30, %31}, {%32, %33, %34, %35}, db, p, 1, 1, 0;\n}\n"
    : "+f"(d[0]), "+f"(d[1]), "+f"(d[2]), "+f"(d[3]), "+f"(d[4]), "+f"(d[5]), "+f"(d[6]), "+f"(d[7]), "+f"(d[8]), "+f"(d[9]), "+f"(d[10]), "+f"(d[11]), "+f"(d[12]), "+f"(d[13]), "+f"(d[14]), "+f"(d[15]), "+f"(d[16]), "+f"(d[17]), "+f"(d[18]), "+f"(d[19]), "+f"(d[20]), "+f"(d[21]), "+f"(d[22]), "+f"(d[23]), "+f"(d[24]), "+f"(d[25]), "+f"(d[26]), "+f"(d[27]), "+f"(d[28]), "+f"(d[29]), "+f"(d[30]), "+f"(d[31])
    : "r"(a0), "r"(a1), "r"(a2), "r"(a3), "r"(blo), "r"(sd));
}
__device__ __forceinline__ void mma_pv(float (&d)[20], uint32_t a0, uint32_t a1, uint32_t a2, uint32_t a3, uint32_t blo, uint32_t sd) {
  asm volatile("{\n.reg .pred p;\n.reg .b64 db;\nsetp.ne.b32 p, %25, 0;\nmov.b64 db, {%24, 0x80000020};\n"
    "wgmma.mma_async.sync.aligned.m64n40k16.f32.bf16.bf16 {%0, %1, %2, %3, %4, %5, %6, %7, %8, %9, %10, %11, %12, %13, %14, %15, %16, %17, %18, %19}, {%20, %21, %22, %23}, db, p, 1, 1, 1;\n}\n"
    : "+f"(d[0]), "+f"(d[1]), "+f"(d[2]), "+f"(d[3]), "+f"(d[4]), "+f"(d[5]), "+f"(d[6]), "+f"(d[7]), "+f"(d[8]), "+f"(d[9]), "+f"(d[10]), "+f"(d[11]), "+f"(d[12]), "+f"(d[13]), "+f"(d[14]), "+f"(d[15]), "+f"(d[16]), "+f"(d[17]), "+f"(d[18]), "+f"(d[19])
    : "r"(a0), "r"(a1), "r"(a2), "r"(a3), "r"(blo), "r"(sd));
}
__device__ __forceinline__ void mma_cs(float (&d)[32], uint32_t a0, uint32_t a1, uint32_t a2, uint32_t a3, uint32_t blo, uint32_t sd) {
  asm volatile("{\n.reg .pred p;\n.reg .b64 db;\nsetp.ne.b32 p, %37, 0;\nmov.b64 db, {%36, 0x40000040};\n"
    "wgmma.mma_async.sync.aligned.m64n64k16.f32.bf16.bf16 {%0, %1, %2, %3, %4, %5, %6, %7, %8, %9, %10, %11, %12, %13, %14, %15, %16, %17, %18, %19, %20, %21, %22, %23, %24, %25, %26, %27, %28, %29, %30, %31}, {%32, %33, %34, %35}, db, p, 1, 1, 1;\n}\n"
    : "+f"(d[0]), "+f"(d[1]), "+f"(d[2]), "+f"(d[3]), "+f"(d[4]), "+f"(d[5]), "+f"(d[6]), "+f"(d[7]), "+f"(d[8]), "+f"(d[9]), "+f"(d[10]), "+f"(d[11]), "+f"(d[12]), "+f"(d[13]), "+f"(d[14]), "+f"(d[15]), "+f"(d[16]), "+f"(d[17]), "+f"(d[18]), "+f"(d[19]), "+f"(d[20]), "+f"(d[21]), "+f"(d[22]), "+f"(d[23]), "+f"(d[24]), "+f"(d[25]), "+f"(d[26]), "+f"(d[27]), "+f"(d[28]), "+f"(d[29]), "+f"(d[30]), "+f"(d[31])
    : "r"(a0), "r"(a1), "r"(a2), "r"(a3), "r"(blo), "r"(sd));
}

template <int NP> __device__ __forceinline__ void mma_g(float (&d)[128], uint32_t a, uint32_t b, uint32_t sd) {
  if constexpr (NP == 2) mma_ss_n128(d, a, b, sd);
  else if constexpr (NP == 3) mma_ss_n192(d, a, b, sd);
  else mma_ss_n256(d, a, b, sd);
}

struct Att {
  float S[32];
  uint32_t P[16];
  float O[20];
  uint32_t Q[8];
  float m0, m1;
  uint32_t j;
  uint32_t kvs;
  uint32_t kvph;
  uint32_t relk;
  uint32_t kd, vd;
  uint32_t safe;
};
struct Ctx {
  uint32_t sb;
  uint32_t wg;
  uint32_t t;
  uint32_t gs;
  uint32_t gph;
  uint32_t lo;
  uint32_t rb;
  uint32_t relg;
  uint32_t da, db;
};
#define T2BEGIN
#define T2END(f)
#define T2DUMP(i)

template <bool P32> __device__ __forceinline__ void ring_next(Ctx& x) {
  if (++x.gs == (P32 ? 6u : 4u)) { x.gs = x.lo; x.gph ^= 1; }
}
template <bool P32> __device__ __forceinline__ uint32_t slot_addr(const Ctx& x) { return x.sb + x.gs * (P32 ? 32768u : 49152u); }
template <bool P32> __device__ __forceinline__ uint32_t full_bar(const Ctx& x) { return x.sb + (P32 ? B_FULL32 : B_FULL48) + x.gs * 8; }
template <bool P32> __device__ __forceinline__ void release_prev(const Ctx& x, bool on) {
  const uint32_t ps = x.gs == x.lo ? (P32 ? 5u : 3u) : x.gs - 1;
  if (x.t < 2 && on) mbar_arrive_remote(x.rb + (P32 ? B_EMPTY32 : B_EMPTY48) + ps * 8);
}
template <bool P32> __device__ __forceinline__ uint32_t desc_a(const Ctx& x) { return (((slot_addr<P32>(x) & 0x3FFFFu) + x.wg * 8192) >> 4) + (1u << 16); }
template <bool P32> __device__ __forceinline__ uint32_t desc_b(const Ctx& x) { return (((slot_addr<P32>(x) & 0x3FFFFu) + 16384) >> 4) + (512u << 16); }
__device__ __forceinline__ uint32_t lane_off64(const Ctx& x) {
  const uint32_t lane = x.t & 31;
  return ((x.t >> 5) * 16 + (lane & 7) + (lane & 8)) * 64 + (((lane >> 4) ^ ((lane & 7) >> 1)) << 4);
}
__device__ __forceinline__ uint32_t lane_off128(const Ctx& x) {
  const uint32_t lane = x.t & 31;
  return ((x.t >> 5) * 16 + (lane & 7) + (lane & 8)) * 128 + (((lane >> 4) ^ (lane & 7)) << 4);
}

constexpr uint32_t VSTEP = 64u - (64u << 16);
__device__ __forceinline__ void kv_desc(Att& a, const Ctx& x) {
  const uint32_t k16 = (((x.sb & 0x3FFFFu) + OFF_KV) >> 4) + a.kvs * 64;
  a.kd = k16 + (1u << 16);
  a.vd = k16 + 256 + ((((OFF_ONES - OFF_KV - 4096) >> 4) - a.kvs * 64) << 16);
}
__device__ __forceinline__ void load_q(Att& a, const Ctx& x) {
  const uint32_t qa = x.sb + OFF_QO + x.wg * 4096 + (x.t >> 5) * 1024 + (x.t & 31) * 16;
  lds128(qa, a.Q[0], a.Q[1], a.Q[2], a.Q[3]);
  lds128(qa + 512, a.Q[4], a.Q[5], a.Q[6], a.Q[7]);
}

template <int NP, int G0, int GN, bool P32, int BM = 0>
__device__ __forceinline__ void att_step(float (&acc)[128], Att& a, Ctx& x, bool first_kb, bool last_kb) {
  const uint32_t jm = a.j & 31;
#pragma unroll
  for (int i = 0; i < 16; i++) a.P[i] = pack2(a.S[2 * i], a.S[2 * i + 1]);
  pin_u(a.P);
  wg_fence();
  mma_pv(a.O, a.P[0], a.P[1], a.P[2], a.P[3], a.vd, jm != 1);
  mma_pv(a.O, a.P[4], a.P[5], a.P[6], a.P[7], a.vd + VSTEP, 1);
  mma_pv(a.O, a.P[8], a.P[9], a.P[10], a.P[11], a.vd + 2 * VSTEP, 1);
  mma_pv(a.O, a.P[12], a.P[13], a.P[14], a.P[15], a.vd + 3 * VSTEP, 1);
  mma_qk(a.S, a.Q[0], a.Q[1], a.Q[2], a.Q[3], a.kd, 0);
  mma_qk(a.S, a.Q[4], a.Q[5], a.Q[6], a.Q[7], a.kd + 2, 1);
  wg_commit();
#pragma unroll
  for (int g = G0; g < G0 + GN; g++) mma_g<NP>(acc, x.da + 2 * g, x.db + 128 * g, g == 0 ? (uint32_t)!first_kb : 1u);
  wg_commit();
  { T2BEGIN wg_wait<1>(); T2END(tw) }
  pin_f(a.S); pin_f(a.O); pin_u(a.P); pin_u(a.Q);
  if constexpr (!(BM & 2)) {
  if (x.t < 2) mbar_arrive_remote(a.relk);
  if constexpr (G0 == 0) { if (x.t < 2 && !first_kb) mbar_arrive_remote(x.relg); }
  }
  const bool rare = (BM & 1) ? false : (BM ? a.safe : (jm == 0 || a.safe));
  if (__builtin_expect(rare, 0)) {
    if (jm == 0) {
      if (a.j != 0) {
        const float l0 = rcp(a.O[16]), l1 = rcp(a.O[18]);
        const uint32_t ad = x.sb + OFF_QO + x.wg * 4096 + lane_off64(x);
        stsm4(ad, pack2(a.O[0] * l0, a.O[1] * l0), pack2(a.O[2] * l1, a.O[3] * l1), pack2(a.O[4] * l0, a.O[5] * l0), pack2(a.O[6] * l1, a.O[7] * l1));
        stsm4(ad ^ 32, pack2(a.O[8] * l0, a.O[9] * l0), pack2(a.O[10] * l1, a.O[11] * l1), pack2(a.O[12] * l0, a.O[13] * l0), pack2(a.O[14] * l1, a.O[15] * l1));
        fence_async_smem();
        mbar_arrive(x.sb + B_STAGED + x.wg * 96 + (EV_O0 - 1 + (a.j >> 5)) * 8);
      }
      a.m0 = -INFINITY; a.m1 = -INFINITY;
      a.safe = lds32(x.sb + OFF_SAFE + ((a.j >> 5) & 3) * 4);
    }
    if (a.safe) {
      float x0 = a.m0, x1 = a.m1;
#pragma unroll
      for (int i = 0; i < 8; i++) { x0 = fmaxf(x0, fmaxf(a.S[4 * i], a.S[4 * i + 1])); x1 = fmaxf(x1, fmaxf(a.S[4 * i + 2], a.S[4 * i + 3])); }
      x0 = fmaxf(x0, __shfl_xor_sync(0xffffffffu, x0, 1)); x1 = fmaxf(x1, __shfl_xor_sync(0xffffffffu, x1, 1));
      x0 = fmaxf(x0, __shfl_xor_sync(0xffffffffu, x0, 2)); x1 = fmaxf(x1, __shfl_xor_sync(0xffffffffu, x1, 2));
      const float s0 = ex2(a.m0 - x0), s1 = ex2(a.m1 - x1);
      a.m0 = x0; a.m1 = x1;
#pragma unroll
      for (int i = 0; i < 5; i++) { a.O[4 * i] *= s0; a.O[4 * i + 1] *= s0; a.O[4 * i + 2] *= s1; a.O[4 * i + 3] *= s1; }
#pragma unroll
      for (int i = 0; i < 8; i++) { a.S[4 * i] -= x0; a.S[4 * i + 1] -= x0; a.S[4 * i + 2] -= x1; a.S[4 * i + 3] -= x1; }
    }
  }
  pin_f(a.S); pin_f(a.O);
  uint32_t ok = 1;
  if constexpr (!(BM & 4)) {
  a.kvs += 8;
  if (a.kvs == 24) { a.kvs = 0; a.kvph ^= 1; }
  kv_desc(a, x);
  a.relk = x.rb + B_KVEMPTY + a.kvs;
  ok = mbar_test(x.sb + B_KVFULL + a.kvs, a.kvph);
  }
  if constexpr (G0 + GN == 4 && !(BM & 4)) {
    x.relg = x.rb + (P32 ? B_EMPTY32 : B_EMPTY48) + x.gs * 8;
    ring_next<P32>(x);
    x.da = desc_a<P32>(x); x.db = desc_b<P32>(x);
    ok &= mbar_test(full_bar<P32>(x), x.gph) | (uint32_t)last_kb;
  }
  if (jm == 31 && !BM) ok = 0;
  if (BM) ok |= (a.j != 1000);
  asm volatile("" : "+r"(a.kd), "+r"(a.vd), "+r"(x.da), "+r"(x.db), "+r"(a.relk), "+r"(x.relg)::"memory");
#pragma unroll
  for (int i = 0; i < 32; i++) a.S[i] = ex2(a.S[i]);
  pin_f(a.S);
  if (__builtin_expect(!ok, 0)) {
    { T2BEGIN mbar_wait(x.sb + B_KVFULL + a.kvs, a.kvph); T2END(tk) }
    if constexpr (G0 + GN == 4) { if (!last_kb) { T2BEGIN mbar_wait(full_bar<P32>(x), x.gph); T2END(tg) } }
    if (jm == 31 && a.j != 127) load_q(a, x);
  }
  pin_u(a.Q);
  a.j++;
}

template <int NP, bool P32>
__device__ __forceinline__ void seg_gemm(float (&acc)[128], Ctx& x, int kb0, int kb1) {
#pragma unroll 1
  for (int kb = kb0; kb < kb1; kb++) {
    { T2BEGIN mbar_wait(full_bar<P32>(x), x.gph); T2END(tg) }
    const uint32_t da = desc_a<P32>(x), db = desc_b<P32>(x);
    wg_fence();
#pragma unroll
    for (int g = 0; g < 4; g++) mma_g<NP>(acc, da + 2 * g, db + 128 * g, g == 0 ? (uint32_t)(kb != 0) : 1u);
    wg_commit();
    { T2BEGIN wg_wait<1>(); T2END(tw) }
    release_prev<P32>(x, kb != 0);
    ring_next<P32>(x);
  }
}
template <int NP, bool P32, bool FINAL = false>
__device__ __forceinline__ void seg_att(float (&acc)[128], Att& a, Ctx& x, int kb0, int kb1) {
  mbar_wait(full_bar<P32>(x), x.gph);
  x.da = desc_a<P32>(x); x.db = desc_b<P32>(x);
  x.relg = x.rb + (P32 ? B_EMPTY32 : B_EMPTY48) + (x.gs == x.lo ? (P32 ? 5u : 3u) : x.gs - 1) * 8;
#pragma unroll 1
  for (int kb = kb0; kb < kb1; kb++) {
    if constexpr (NP == 4) {
      att_step<NP, 0, 2, P32>(acc, a, x, kb == 0, false);
      att_step<NP, 2, 2, P32>(acc, a, x, false, kb == kb1 - 1);
    } else {
      if constexpr (FINAL) x.lo = kb < 14 ? 2 : 0;
      att_step<NP, 0, 4, P32>(acc, a, x, kb == 0, kb == kb1 - 1);
    }
  }
}
template <int NP> __device__ __forceinline__ void tile_drain(float (&acc)[128]) {
  wg_wait<0>();
  pin_acc<0, NP * 32>(acc);
}
template <bool P32> __device__ __forceinline__ uint32_t transit_buf(const Ctx& x) {
  return x.sb + (x.gs == x.lo ? (P32 ? 5u : 3u) : x.gs - 1) * (P32 ? 32768u : 49152u) + x.wg * 8192;
}

template <int PN> __device__ __forceinline__ void norm_max(const float (&acc)[128], float sc2, uint32_t dst, uint32_t lane) {
#pragma unroll
  for (int h = 0; h < 2; h++) {
    float a = 0.f, b = 0.f;
#pragma unroll
    for (int i = 0; i < 4; i++) {
      const int o = PN * 32 + h * 16 + i * 4;
      a += acc[o] * acc[o] + acc[o + 1] * acc[o + 1];
      b += acc[o + 2] * acc[o + 2] + acc[o + 3] * acc[o + 3];
    }
    a += __shfl_xor_sync(0xffffffffu, a, 1); b += __shfl_xor_sync(0xffffffffu, b, 1);
    a += __shfl_xor_sync(0xffffffffu, a, 2); b += __shfl_xor_sync(0xffffffffu, b, 2);
    const unsigned m = __reduce_max_sync(0xffffffffu, max(__float_as_uint(a * sc2), __float_as_uint(b * sc2)));
    if (lane == 0) sts32(dst + h * 16 + PN * 4, m);
  }
}
__device__ __forceinline__ void epi_qkv(const float (&acc)[128], const Ctx& x, uint32_t stg) {
  constexpr float SC = 0.17677669529663687f * 1.4426950408889634f;
  const uint32_t lane = x.t & 31, nd = x.sb + OFF_NRM + x.wg * 128 + (x.t >> 5) * 32;
  const uint32_t qa = stg + (x.t >> 5) * 1024 + lane * 16;
#pragma unroll
  for (int u = 0; u < 4; u++) {
    const int o = u * 8;
    sts128(qa + (u >> 1) * 4096 + (u & 1) * 512, pack2(acc[o] * SC, acc[o + 1] * SC), pack2(acc[o + 2] * SC, acc[o + 3] * SC),
           pack2(acc[o + 4] * SC, acc[o + 5] * SC), pack2(acc[o + 6] * SC, acc[o + 7] * SC));
  }
  const uint32_t ad = stg + 8192 + lane_off64(x);
#pragma unroll
  for (int u = 0; u < 8; u++) {
    const int o = 32 + u * 8;
    stsm4((ad ^ ((u & 1) << 5)) + (u >> 1) * 4096, pack2(acc[o], acc[o + 1]), pack2(acc[o + 2], acc[o + 3]), pack2(acc[o + 4], acc[o + 5]), pack2(acc[o + 6], acc[o + 7]));
  }
  norm_max<0>(acc, SC * SC, nd, lane);
  norm_max<1>(acc, 1.f, nd, lane);
  norm_max<2>(acc, 1.f, nd, lane);
}
template <int PN> __device__ __forceinline__ void epi_hs(const float (&acc)[128], uint32_t ad) {
#pragma unroll
  for (int b = 0; b < 8; b += 2) {
    const int o = PN * 32 + b * 4;
    stsm4(ad ^ (b << 4), pack2_relu(acc[o], acc[o + 1]), pack2_relu(acc[o + 2], acc[o + 3]), pack2_relu(acc[o + 4], acc[o + 5]), pack2_relu(acc[o + 6], acc[o + 7]));
  }
}
template <int PN> __device__ __forceinline__ void epi_h(const float (&acc)[128], const Ctx& x, uint32_t buf, uint8_t* dst) {
  const uint32_t ad = buf + lane_off128(x), lo = (x.t >> 5) * 2048 + (x.t & 31) * 16;
#pragma unroll
  for (int b = 0; b < 8; b += 2) {
    const int o = PN * 32 + b * 4;
    stsm4(ad ^ (b << 4), pack2_relu(acc[o], acc[o + 1]), pack2_relu(acc[o + 2], acc[o + 3]), pack2_relu(acc[o + 4], acc[o + 5]), pack2_relu(acc[o + 6], acc[o + 7]));
  }
  __syncwarp();
#pragma unroll
  for (int i = 0; i < 4; i++) {
    uint4 v;
    lds128(buf + lo + i * 512, v.x, v.y, v.z, v.w);
    __stcg(reinterpret_cast<uint4*>(dst + lo + i * 512), v);
  }
  __syncwarp();
}
template <int PN> __device__ __forceinline__ void epi_out(const float (&acc)[128], uint32_t ad) {
#pragma unroll
  for (int b = 0; b < 8; b += 2) {
    const int o = PN * 32 + b * 4;
    uint32_t r0, r1, r2, r3;
    ldsm4(ad ^ (b << 4), r0, r1, r2, r3);
    stsm4(ad ^ (b << 4), pack2(acc[o] + bf_lo(r0), acc[o + 1] + bf_hi(r0)), pack2(acc[o + 2] + bf_lo(r1), acc[o + 3] + bf_hi(r1)),
          pack2(acc[o + 4] + bf_lo(r2), acc[o + 5] + bf_hi(r2)), pack2(acc[o + 6] + bf_lo(r3), acc[o + 7] + bf_hi(r3)));
  }
}
template <bool P32> __device__ __forceinline__ void staged(Ctx& x, uint32_t ev) {
  fence_async_smem();
  mbar_arrive(x.sb + B_STAGED + x.wg * 96 + ev * 8);
  ring_next<P32>(x);
}

__device__ __forceinline__ float2 row_stats(const uint4 (&v)[4]) {
  float s = 0.f;
#pragma unroll
  for (int i = 0; i < 4; i++)
    s += (bf_lo(v[i].x) + bf_hi(v[i].x)) + (bf_lo(v[i].y) + bf_hi(v[i].y)) + (bf_lo(v[i].z) + bf_hi(v[i].z)) + (bf_lo(v[i].w) + bf_hi(v[i].w));
#pragma unroll
  for (int o = 16; o; o >>= 1) s += __shfl_xor_sync(0xffffffffu, s, o);
  const float mean = s * (1.f / 1024.f);
  float q0 = 0.f, q1 = 0.f;
#pragma unroll
  for (int i = 0; i < 4; i++) {
    const uint32_t u[4] = {v[i].x, v[i].y, v[i].z, v[i].w};
#pragma unroll
    for (int k = 0; k < 4; k++) { const float d0 = bf_lo(u[k]) - mean, d1 = bf_hi(u[k]) - mean; q0 += d0 * d0; q1 += d1 * d1; }
  }
  float q = q0 + q1;
#pragma unroll
  for (int o = 16; o; o >>= 1) q += __shfl_xor_sync(0xffffffffu, q, o);
  const float sd = bf_round(sqrtf(bf_round(bf_round(q * (1.f / 1024.f)) + 1e-5f)));
  return make_float2(bf_round(mean), 1.f / sd);
}
__device__ __forceinline__ void row_stage(const uint4 (&v)[4], float2 st, uint32_t stg, uint32_t r, uint32_t lane) {
#pragma unroll
  for (int i = 0; i < 4; i++) {
    const uint32_t ci = lane + 32 * i;
    sts128(stg + (ci >> 3) * 2048 + r * 128 + (((ci & 7) ^ (r & 7)) << 4),
           pack2((bf_lo(v[i].x) - st.x) * st.y, (bf_hi(v[i].x) - st.x) * st.y), pack2((bf_lo(v[i].y) - st.x) * st.y, (bf_hi(v[i].y) - st.x) * st.y),
           pack2((bf_lo(v[i].z) - st.x) * st.y, (bf_hi(v[i].z) - st.x) * st.y), pack2((bf_lo(v[i].w) - st.x) * st.y, (bf_hi(v[i].w) - st.x) * st.y));
  }
}

__device__ __forceinline__ uint32_t need_safe(uint32_t head, uint32_t lane) {
  const uint4* t = g_nrm + (head >> 1) * 256 + (head & 1) + lane * 2;
  unsigned nq = 0, nk = 0, nv = 0;
#pragma unroll
  for (int i = 0; i < 4; i++) {
    const uint4 e = __ldcg(t + i * 64);
    nq = max(nq, e.x); nk = max(nk, e.y); nv = max(nv, e.z);
  }
  const float fq = __uint_as_float(__reduce_max_sync(0xffffffffu, nq)), fk = __uint_as_float(__reduce_max_sync(0xffffffffu, nk));
  const float fv = __uint_as_float(__reduce_max_sync(0xffffffffu, nv));
  const bool ok = (fq * fk <= 3900.f) && (fq <= 1e18f) && (fk <= 1e18f) && (fv <= 1e24f) && (fv >= 1e-24f);
  return ok ? 0u : 1u;
}

__device__ __forceinline__ void colsum_half(uint32_t sb, uint32_t c, uint32_t w, uint32_t lane) {
  if (lane < 24) {
    const float4* src = reinterpret_cast<const float4*>(g_csp + c * 8 * 192 + w * 96) + lane;
    float4 t = make_float4(0.f, 0.f, 0.f, 0.f);
#pragma unroll
    for (int h = 0; h < 2; h++) {
      float4 e[4];
#pragma unroll
      for (int i = 0; i < 4; i++) e[i] = __ldcg(src + (h * 4 + i) * 48);
#pragma unroll
      for (int i = 0; i < 4; i++) { t.x += e[i].x; t.y += e[i].y; t.z += e[i].z; t.w += e[i].w; }
    }
    sts128(sb + OFF_CS + w * 384 + lane * 16, __float_as_uint(t.x), __float_as_uint(t.y), __float_as_uint(t.z), __float_as_uint(t.w));
  }
  __syncwarp();
  if (lane == 0) mbar_arrive(sb + B_LNRDY);
}

__device__ __forceinline__ uint32_t item_head(uint32_t item, uint32_t c) { return item < 2 ? 2 * c + item : item * 8 + c; }

struct Maps { CUtensorMap wqkv, w1, w2, wo, o_st, o_ld, x, out; };

__global__ void __launch_bounds__(384, 1) fused_block_kernel(const __grid_constant__ Maps mp, const __nv_bfloat16* __restrict__ xin) {
  extern __shared__ __align__(1024) uint8_t smem[];
  const uint32_t sb = (uint32_t)__cvta_generic_to_shared(smem);
  const uint32_t tid = threadIdx.x;
  const uint32_t wg = __shfl_sync(0xffffffffu, tid >> 7, 0);
  uint32_t rank;
  asm("mov.u32 %0, %%cluster_ctarank;" : "=r"(rank));
  const uint32_t cid = blockIdx.x >> 1, p = cid >> 3, c = cid & 7, mt = 2 * p + rank;
  const uint32_t fm = cid >> 2, fn = (cid & 3) * 2 + rank;
  MARK(0);
  if (tid == 256) {
    if (sb & 1023) __trap();
    for (int i = 0; i < 4; i++) { mbar_init(sb + B_FULL48 + 8 * i, 1); mbar_init(sb + B_EMPTY48 + 8 * i, 4); }
    for (int i = 0; i < 6; i++) { mbar_init(sb + B_FULL32 + 8 * i, 1); mbar_init(sb + B_EMPTY32 + 8 * i, 4); }
    for (int i = 0; i < 3; i++) { mbar_init(sb + B_KVFULL + 8 * i, 1); mbar_init(sb + B_KVEMPTY + 8 * i, 4); }
    for (int i = 0; i < 24; i++) mbar_init(sb + B_STAGED + 8 * i, 128);
    for (int i = 0; i < 3; i++) mbar_init(sb + B_OFREE + 8 * i, 2);
    for (int i = 0; i < 2; i++) mbar_init(sb + B_STGFREE + 8 * i, 1);
    mbar_init(sb + B_STGFREE + 16, 4);
    mbar_init(sb + B_LNRDY, 2);
    mbar_init(sb + B_XNDONE, 2);
    for (int i = 0; i < 5; i++) {
      mbar_arrive(sb + B_FULL32 + 8 * i);
      for (int k = 0; k < 4; k++) mbar_arrive(sb + B_EMPTY32 + 8 * i);
    }
    asm volatile("fence.mbarrier_init.release.cluster;" ::: "memory");
  }
  __syncwarp();
  asm volatile("barrier.cluster.arrive.release.aligned;" ::: "memory");

  if (wg == 2) {
    asm volatile("setmaxnreg.dec.sync.aligned.u32 40;");
    asm volatile("barrier.cluster.wait.acquire.aligned;" ::: "memory");
    const uint32_t warp = __shfl_sync(0xffffffffu, (tid >> 5) & 3, 0);
    if (warp == 2) {
      uint32_t s = 0, ph = 1;
      const uint8_t* xa = g_xn + mt * 16 * 16384;
      const uint32_t boff = 16384 + rank * 4096;
      uint32_t lo = 0;
      auto next48 = [&]() { if (++s == 4) { s = lo; ph ^= 1; } };
      auto next32 = [&]() { if (++s == 6) { s = lo; ph ^= 1; } };
#pragma unroll 1
      for (int i = 0; i < 16; i++) {
        const int kb = (i >> 1) == 3 ? 2 * p + (i & 1) : (i >> 1) == (int)p ? 6 + (i & 1) : i;
        const uint32_t dst = sb + s * 49152, fb = sb + B_FULL48 + s * 8;
        mbar_wait(sb + B_EMPTY48 + s * 8, ph);
        if (elect_one()) {
          mbar_expect(fb, 40960);
          tma2d(dst, &mp.x, kb * 64, mt * 128, fb);
          tma2d(dst + 8192, &mp.x, kb * 64, mt * 128 + 64, fb);
#pragma unroll
          for (int u = 0; u < 3; u++) tma2d_mc(dst + boff + u * 8192, &mp.wqkv, c * 64 + u * 1024, kb * 64 + rank * 32, fb);
          if (i == PFX) {
            bulk_prefetch(xin + (size_t)(mt * 128 + c * 16) * 1024, 32768);
#pragma unroll
            for (int u = 0; u < 6; u++) tma2d_pf(&mp.wqkv, c * 64 + (u >> 1) * 1024, mt * 64 + (u & 1) * 32);
          }
          if (PF && (i == 10 || i == 11)) {
            const int kr = (2 * p + i - 10) * 64 + rank * 32;
#pragma unroll
            for (int u = 0; u < 3; u++) tma2d_pf(&mp.wqkv, (8 + c) * 64 + u * 1024, kr);
            tma2d_pf(&mp.w1, c * 64, kr);
          }
        }
        next48();
      }
      poll_ge(&g_sync.ln[mt * 8], 8);
      s = 1; lo = 1;
#pragma unroll 1
      for (int kb = 0; kb < 16; kb++) {
        const uint32_t dst = sb + s * 49152, fb = sb + B_FULL48 + s * 8;
        mbar_wait(sb + B_EMPTY48 + s * 8, ph);
        if (elect_one()) {
          mbar_expect(fb, 49152);
          bulk_ld(dst, xa + kb * 16384, 16384, fb);
#pragma unroll
          for (int i = 0; i < 3; i++) tma2d_mc(dst + boff + i * 8192, &mp.wqkv, (8 + c) * 64 + i * 1024, kb * 64 + rank * 32, fb);
          tma2d_mc(dst + boff + 24576, &mp.w1, c * 64, kb * 64 + rank * 32, fb);
          if (PF && (kb & 7) == p) {
#pragma unroll
            for (int i = 0; i < 4; i++) tma2d_pf(&mp.w1, (i < 3 ? 8 + 3 * c + i : 32 + c) * 64, kb * 64 + rank * 32);
          }
        }
        next48();
      }
#pragma unroll 1
      for (int kb = 0; kb < 16; kb++) {
        const uint32_t dst = sb + s * 49152, fb = sb + B_FULL48 + s * 8;
        mbar_wait(sb + B_EMPTY48 + s * 8, ph);
        if (elect_one()) {
          mbar_expect(fb, 49152);
          bulk_ld(dst, xa + kb * 16384, 16384, fb);
#pragma unroll
          for (int i = 0; i < 4; i++) tma2d_mc(dst + boff + i * 8192, &mp.w1, (i < 3 ? 8 + 3 * c + i : 32 + c) * 64, kb * 64 + rank * 32, fb);
          if (PF && (kb & 7) == p) {
            tma2d_pf(&mp.w1, (40 + 2 * c) * 64, kb * 64 + rank * 32);
            tma2d_pf(&mp.w1, (41 + 2 * c) * 64, kb * 64 + rank * 32);
          }
        }
        next48();
      }
      s = 5; ph = 1; lo = 2;
#pragma unroll 1
      for (int kb = 0; kb < 16; kb++) {
        const uint32_t dst = sb + s * 32768, fb = sb + B_FULL32 + s * 8;
        if (kb == 0) mbar_wait(sb + B_EMPTY48 + 24, 1);
        if (kb == 1 || kb == 2) mbar_wait(sb + B_EMPTY48 + kb * 8, 0);
        mbar_wait(sb + B_EMPTY32 + s * 8, ph);
        if (elect_one()) {
          mbar_expect(fb, 32768);
          bulk_ld(dst, xa + kb * 16384, 16384, fb);
          tma2d_mc(dst + boff, &mp.w1, (40 + 2 * c) * 64, kb * 64 + rank * 32, fb);
          tma2d_mc(dst + boff + 8192, &mp.w1, (41 + 2 * c) * 64, kb * 64 + rank * 32, fb);
          if (PF && kb == (int)fm) {
            tma2d_pf(&mp.w2, fn * 128, kb * 64);
            tma2d_pf(&mp.w2, fn * 128 + 64, kb * 64);
          }
        }
        next32();
      }
      const uint8_t* ha = g_h + fm * 56 * 16384 + rank * 8192;
#pragma unroll 1
      for (int part = 0; part < 4; part++) {
        const unsigned* cnt = part == 0 ? &g_sync.hA[fm * 8] : part == 1 ? &g_sync.hB[fm * 8] : part == 2 ? &g_sync.oc[(fm * 4 + 1) * 8] : &g_sync.hC[fm * 8];
        const unsigned seen = peek(cnt);
        if (part == 2) mbar_wait(sb + B_STGFREE + 16, 0);
        mbar_wait(sb + B_EMPTY32 + s * 8, ph);
        confirm(cnt, seen, 16);
        const int kb1 = part == 0 ? 8 : part == 1 ? 17 : part == 2 ? 32 : 56;
#pragma unroll 1
        for (int kb = part == 0 ? 0 : part == 1 ? 8 : part == 2 ? 17 : 32; kb < kb1; kb++) {
          const uint32_t dst = sb + s * 32768, fb = sb + B_FULL32 + s * 8;
          mbar_wait(sb + B_EMPTY32 + s * 8, ph);
          if (elect_one()) {
            mbar_expect(fb, 32768);
            bulk_ld_mc(dst + rank * 8192, ha + kb * 16384, 8192, fb);
            tma2d(dst + 16384, &mp.w2, fn * 128, kb * 64, fb);
            tma2d(dst + 24576, &mp.w2, fn * 128 + 64, kb * 64, fb);
            if (PF && (kb & 15) == (int)fm) {
              const CUtensorMap* m = kb < 40 ? &mp.w2 : &mp.wo;
              const int kr = (kb < 40 ? kb + 16 : kb - 40) * 64;
              tma2d_pf(m, fn * 128, kr);
              tma2d_pf(m, fn * 128 + 64, kr);
            }
          }
          if (kb == 14) lo = 0;
          next32();
        }
      }
#pragma unroll 1
      for (int r = 0; r < 4; r++) {
        const unsigned* cnt = &g_sync.oc[(fm * 4 + (r == 1 ? 0 : r)) * 8];
        const unsigned seen = peek(cnt);
        mbar_wait(sb + B_EMPTY32 + s * 8, ph);
        confirm(cnt, seen, 16);
#pragma unroll 1
        for (int kb = r * 4; kb < r * 4 + 4; kb++) {
          const uint32_t dst = sb + s * 32768, fb = sb + B_FULL32 + s * 8;
          mbar_wait(sb + B_EMPTY32 + s * 8, ph);
          if (elect_one()) {
            mbar_expect(fb, 32768);
            tma2d_mc(dst + rank * 8192, &mp.o_ld, kb * 64, fm * 128 + rank * 64, fb);
            tma2d(dst + 16384, &mp.wo, fn * 128, kb * 64, fb);
            tma2d(dst + 24576, &mp.wo, fn * 128 + 64, kb * 64, fb);
          }
          next32();
        }
      }
      mbar_wait(sb + B_EMPTY32 + s * 8, ph);
      if (elect_one()) {
        const uint32_t fb = sb + B_FULL32 + s * 8;
        mbar_expect(fb, 32768);
#pragma unroll
        for (int i = 0; i < 4; i++) tma2d(sb + s * 32768 + i * 8192, &mp.x, fn * 128 + (i >> 1) * 64, fm * 128 + (i & 1) * 64, fb);
      }
      unsigned ticket = 0;
      if ((tid & 31) == 0) ticket = atomicAdd(&g_sync.done[0], 1u);
      if (__shfl_sync(0xffffffffu, ticket, 0) == NCTA - 1) {
        uint4* z = reinterpret_cast<uint4*>(&g_sync);
        for (uint32_t i = tid & 31; i < sizeof(Sync) / 16; i += 32) z[i] = make_uint4(0, 0, 0, 0);
      }
    } else if (warp == 3) {
      uint32_t s = 0, ph = 1;
      const uint8_t* const kvb = rank == 0 ? g_k : g_v;
      const uint8_t* src = kvb + 2 * c * 32 * 4096;
      const uint32_t dst = sb + OFF_KV + rank * 4096;
      mbar_wait(sb + B_STAGED + EV_LN * 8, 0);
      mbar_wait(sb + B_STAGED + 96 + EV_LN * 8, 0);
#pragma unroll 1
      for (int kb = 0; kb < 16; kb++) {
        if (elect_one()) bulk_st(g_xn + (mt * 16 + kb) * 16384 + c * 2048, sb + OFF_KV + kb * 2048, 2048);
        __nanosleep(XPACE);
      }
      if (elect_one()) {
        bulk_commit();
        bulk_wait<0>();
        signal_relaxed(&g_sync.ln[mt * 8]);
        mbar_arrive_remote(mapa(sb + B_XNDONE, 0));
        mbar_arrive_remote(mapa(sb + B_XNDONE, 1));
      }
      mbar_wait(sb + B_XNDONE, 0);
      MARKP(12);
      poll_ge(&g_sync.qkv[2 * c * 8], 32);
      MARKP(11);
      auto stage = [&](bool adv) {
        mbar_wait(sb + B_KVEMPTY + s * 8, ph);
        if (elect_one()) {
          mbar_expect(sb + B_KVFULL + s * 8, 8192);
          bulk_ld_mc(dst + s * 8192, src, 4096, sb + B_KVFULL + s * 8);
        }
        if (adv) src += 4096;
        if (++s == 3) { s = 0; ph ^= 1; }
      };
#pragma unroll 1
      for (int item = 0; item < 4; item++) {
        if (item >= 2) mbar_wait(sb + B_OFREE + (item - 2) * 8, 0);
        mbar_wait(sb + B_KVEMPTY + s * 8, ph);
        if (elect_one()) {
          asm volatile("mbarrier.expect_tx.relaxed.cta.shared::cta.b64 [%0], 8192;" ::"r"(sb + B_KVFULL + s * 8) : "memory");
          bulk_ld(sb + OFF_QO, g_q + (item_head(item, c) * 32 + mt * 2) * 4096, 8192, sb + B_KVFULL + s * 8);
        }
        if (item == 0) {
          if (elect_one()) {
            asm volatile("mbarrier.expect_tx.relaxed.cta.shared::cta.b64 [%0], 8192;" ::"r"(sb + B_KVFULL) : "memory");
            bulk_ld_mc(dst, src, 4096, sb + B_KVFULL);
          }
          sts32(sb + OFF_SAFE, need_safe(2 * c, tid & 31));
          __syncwarp();
          if (elect_one()) mbar_arrive(sb + B_KVFULL);
          if (rank == 0) src += 4096;
          s = 1;
        } else {
          stage(true);
        }
        if (rank == 1 && item != 0) src = kvb + item_head(item, c) * 32 * 4096;
#pragma unroll 1
        for (int j = 1; j < 32; j++) {
          stage(true);
          if (j == 22 && item < 3) {
            poll_ge(&g_sync.qkv[(item == 0 ? 2 * c + 1 : 12 + item * 4 + (c >> 1)) * 8], 32);
            sts32(sb + OFF_SAFE + item * 4 + 4, need_safe(item_head(item + 1, c), tid & 31));
          }
        }
        if (rank == 0) src = item == 3 ? src - 4096 : kvb + item_head(item + 1, c) * 32 * 4096;
      }
      stage(false);
      stage(false);
    } else {
      const uint32_t w = warp, st = sb + B_STAGED + w * 96, rt = mt * 2 + w;
            uint8_t* hb = g_h + mt * 56 * 16384 + w * 8192;
      const bool lead = elect_one();
      const uint32_t rb0 = mapa(sb, 0), rb1 = mapa(sb, 1);
      auto release = [&](uint32_t bar) { if (lead) { mbar_arrive_remote(rb0 + bar); mbar_arrive_remote(rb1 + bar); } };
      auto copy_out = [&](uint8_t* dst, uint32_t src, int bytes) {
#pragma unroll 1
        for (int o = 0; o < bytes; o += CHUNK) {
          if (lead) bulk_st(dst + o, src + o, CHUNK);
          __nanosleep(PACE);
        }
      };
      auto copy_done = [&]() { if (lead) { bulk_commit(); bulk_wait<0>(); } };
      auto o_event = [&](uint32_t r) {
        mbar_wait(st + (EV_O0 + r) * 8, 0);
        if (lead) {
          tma2d_st(&mp.o_st, item_head(r, c) * 32, rt * 64, sb + OFF_QO + w * 4096);
          bulk_commit();
          bulk_wait<0>();
          if (r < 2) mbar_arrive(sb + B_OFREE + r * 8);
          signal_relaxed(&g_sync.oc[(mt * 4 + r) * 8]);
        }
      };
      sts128(sb + OFF_ONES + w * 512 + (tid & 31) * 16, 0x3f803f80u, 0x3f803f80u, 0x3f803f80u, 0x3f803f80u);
      fence_async_smem();
      mbar_wait(st + EV_CS * 8, 0);
      if (lead) {
        if (rank * 2 + w < 3) bulk_st(g_csp + (c * 8 + p) * 192 + (rank * 2 + w) * 64, sb + 40960 + w * 512, 256);
        bulk_st(g_stat + mt * 128 + c * 16 + w * 8, sb + 40960 + w * 512 + 256, 64);
        bulk_commit();
        bulk_wait<0>();
        signal_relaxed(&g_sync.cs[c * 8]);
        signal_relaxed(&g_sync.st[mt * 8]);
      }
      __syncwarp();
      if (w == 0) poll_ge(&g_sync.st[mt * 8], 16);
      poll_ge(&g_sync.cs[c * 8], 32);
      colsum_half(sb, c, w, tid & 31);
      MARKS(13);
      mbar_wait(st + EV_T1 * 8, 0);
      MARKS(1);
      if (lead) {
        bulk_st(g_k + (2 * c * 32 + rt) * 4096, sb + w * 24576 + 8192, 4096);
        bulk_st(g_q + (2 * c * 32 + rt) * 4096, sb + w * 24576, 4096);
        bulk_st(g_v + (2 * c * 32 + rt) * 4096, sb + w * 24576 + 16384, 4096);
        bulk_st(g_nrm + (c * 32 + rt) * 8, sb + OFF_NRM + w * 128, 128);
        bulk_commit();
        bulk_wait<0>();
        signal_relaxed(&g_sync.qkv[2 * c * 8]);
      }
      MARKS(3);
      __nanosleep(1500);
#pragma unroll 1
      for (int i = 0; i < 3; i++)
        copy_out((i == 0 ? g_q : i == 1 ? g_k : g_v) + ((2 * c + 1) * 32 + rt) * 4096, sb + w * 24576 + i * 8192 + 4096, 4096);
      copy_done();
      if (lead) { signal_relaxed(&g_sync.qkv[(2 * c + 1) * 8]); mbar_arrive(sb + B_STGFREE + w * 8); }
      mbar_wait(st + EV_T2 * 8, 0);
      MARKS(6);
#pragma unroll 1
      for (int i = 0; i < 6; i++)
        copy_out((i < 2 ? g_q : i < 4 ? g_k : g_v) + ((16 + 2 * c + (i & 1)) * 32 + rt) * 4096, sb + w * 24576 + i * 4096, 4096);
      if (lead) bulk_st(g_nrm + ((8 + c) * 32 + rt) * 8, sb + OFF_NRM + w * 128, 128);
      copy_done();
      MARKS(8);
      if (lead) { mbar_arrive(sb + B_STGFREE + w * 8); signal_relaxed(&g_sync.qkv[(16 + c) * 8]); signal_release(&g_sync.hA[mt * 8]); }
      o_event(0);
      mbar_wait(st + EV_T3 * 8, 0);
#pragma unroll 1
      for (int i = 0; i < 3; i++) copy_out(hb + (8 + 3 * c + i) * 16384, sb + w * 24576 + i * 8192, 8192);
      copy_done();
      if (lead) { mbar_arrive(sb + B_STGFREE + w * 8); signal_relaxed(&g_sync.hB[mt * 8]); }
      o_event(1);
      mbar_wait(st + EV_T4 * 8, 0);
#pragma unroll 1
      for (int i = 0; i < 3; i++) copy_out(hb + (i < 2 ? 40 + 2 * c + i : 32 + c) * 16384, sb + w * 24576 + i * 8192, 8192);
      copy_done();
      release(B_STGFREE + 16);
      if (lead) signal_relaxed(&g_sync.hC[mt * 8]);
      o_event(2);
      o_event(3);
      mbar_wait(st + EV_FIN * 8, 0);
      if (lead) {
        tma2d_st(&mp.out, fn * 128, fm * 128 + w * 64, sb + 32768 + w * 8192);
        tma2d_st(&mp.out, fn * 128 + 64, fm * 128 + w * 64, sb + 32768 + w * 8192 + 16384);
        bulk_commit();
        bulk_wait<0>();
      }
    }
    __syncwarp();
  } else {
    asm volatile("setmaxnreg.inc.sync.aligned.u32 232;");
    MARK(1);
    asm volatile("barrier.cluster.wait.acquire.aligned;" ::: "memory");

    Ctx x{sb, wg, tid & 127, 0, 0, 0, mapa(sb, tid & 1), 0, 0, 0};
    float acc[128];
    Att a;
#pragma unroll
    for (int i = 0; i < 96; i++) acc[i] = 0.f;
    pin_acc<0, 96>(acc);

    uint8_t* const hb = g_h + mt * 56 * 16384 + wg * 8192;
    MARK(3);
    {
      uint4 xv[2][4];
      auto load_x = [&]() {
#pragma unroll
        for (int rr = 0; rr < 2; rr++) {
          const uint4* xr = reinterpret_cast<const uint4*>(xin + (size_t)(mt * 128 + c * 16 + (tid >> 5) * 2 + rr) * 1024);
#pragma unroll
          for (int i = 0; i < 4; i++) xv[rr][i] = __ldg(xr + (tid & 31) + 32 * i);
        }
      };
      seg_gemm<3, false>(acc, x, 0, XPOS);
      MARK(4);
      load_x();
      seg_gemm<3, false>(acc, x, XPOS, 6);
      float cs[32];
#pragma unroll
      for (int i = 0; i < 32; i++) cs[i] = 0.f;
      uint32_t one[4] = {0x3f803f80u, 0x3f803f80u, 0x3f803f80u, 0x3f803f80u};
      pin_f(cs);
      pin_u(one);
      const uint32_t pn = min(rank * 2 + wg, 2u);
      float2 rs[2];
#pragma unroll
      for (int kb = 0; kb < 2; kb++) {
        mbar_wait(full_bar<false>(x), x.gph);
        const uint32_t da = desc_a<false>(x), db = desc_b<false>(x);
        wg_fence();
#pragma unroll
        for (int g = 0; g < 4; g++) mma_cs(cs, one[0], one[1], one[2], one[3], db + pn * 512 + 128 * g, 1);
#pragma unroll
        for (int g = 0; g < 4; g++) mma_ss_n192(acc, da + 2 * g, db + 128 * g, 1);
        wg_commit();
        wg_wait<1>();
        release_prev<false>(x, true);
        ring_next<false>(x);
        rs[kb] = row_stats(xv[kb]);
      }
      seg_gemm<3, false>(acc, x, 8, 9);
      pin_f(cs);
      const uint32_t small = sb + 40960 + wg * 512;
      if (x.t < 4) {
#pragma unroll
        for (int b = 0; b < 8; b++)
          asm volatile("st.shared.v2.f32 [%0], {%1, %2};" ::"r"(small + b * 32 + x.t * 8), "f"(cs[4 * b]), "f"(cs[4 * b + 1]) : "memory");
      }
      if ((tid & 31) == 0) sts128(small + 256 + (x.t >> 5) * 16, __float_as_uint(rs[0].x), __float_as_uint(rs[0].y), __float_as_uint(rs[1].x), __float_as_uint(rs[1].y));
      fence_async_smem();
      mbar_arrive(sb + B_STAGED + wg * 96 + EV_CS * 8);
      row_stage(xv[0], rs[0], sb + OFF_KV, (tid >> 5) * 2, tid & 31);
      seg_gemm<3, false>(acc, x, 9, 10);
      row_stage(xv[1], rs[1], sb + OFF_KV, (tid >> 5) * 2 + 1, tid & 31);
      fence_async_smem();
      mbar_arrive(sb + B_STAGED + wg * 96 + EV_LN * 8);
    }
    seg_gemm<3, false>(acc, x, 10, 16);
    MARK(2);
    mbar_wait(sb + B_LNRDY, 0);
    const float2 st0 = __ldcg(&g_stat[mt * 128 + wg * 64 + (x.t >> 5) * 16 + ((x.t & 31) >> 2)]);
    const float2 st1 = __ldcg(&g_stat[mt * 128 + wg * 64 + (x.t >> 5) * 16 + ((x.t & 31) >> 2) + 8]);
    tile_drain<3>(acc);
#pragma unroll
    for (int b = 0; b < 24; b++) {
      float2 cv;
      asm volatile("ld.shared.v2.f32 {%0, %1}, [%2];" : "=f"(cv.x), "=f"(cv.y) : "r"(sb + OFF_CS + b * 32 + (x.t & 3) * 8));
      acc[4 * b] = (acc[4 * b] - st0.x * cv.x) * st0.y; acc[4 * b + 1] = (acc[4 * b + 1] - st0.x * cv.y) * st0.y;
      acc[4 * b + 2] = (acc[4 * b + 2] - st1.x * cv.x) * st1.y; acc[4 * b + 3] = (acc[4 * b + 3] - st1.x * cv.y) * st1.y;
    }
    release_prev<false>(x, true);
    mbar_wait(sb + B_EMPTY48, 1);
    MARK(5);
    T2DUMP(0);
    epi_qkv(acc, x, sb + wg * 24576);
    fence_async_smem();
    mbar_arrive(sb + B_STAGED + wg * 96 + EV_T1 * 8);
    x.gs = 1; x.lo = 1;
#pragma unroll
    for (int i = 0; i < 32; i++) { a.S[i] = 0.f; acc[96 + i] = 0.f; }
#pragma unroll
    for (int i = 0; i < 16; i++) a.P[i] = 0u;
#pragma unroll
    for (int i = 0; i < 20; i++) a.O[i] = 0.f;
    a.m0 = a.m1 = 0.f;
    a.j = 0; a.kvs = 0; a.kvph = 0; a.safe = 0;
    kv_desc(a, x);
    a.relk = x.rb + B_KVEMPTY;
    pin_f(acc); pin_f(a.S); pin_f(a.O); pin_u(a.P);
    MARK(6);
    seg_gemm<4, false>(acc, x, 0, D1);
    MARK(7);
    mbar_wait(sb + B_KVFULL, 0);
    load_q(a, x);
    pin_u(a.Q);
    MARK(8);
    T2DUMP(1);
    seg_att<4, false>(acc, a, x, D1, 16);
    tile_drain<4>(acc);
    MARK(10);
    T2DUMP(2);
    mbar_wait(sb + B_STGFREE + wg * 8, 0);
    epi_qkv(acc, x, sb + wg * 24576);
    fence_async_smem();
    epi_h<3>(acc, x, transit_buf<false>(x), hb + c * 16384);
    mbar_arrive(sb + B_STAGED + wg * 96 + EV_T2 * 8);
    asm volatile("bar.sync %0, 128;" ::"r"(2 + wg) : "memory");
    release_prev<false>(x, true);
    pin_f(acc);
    MARK(11);
    seg_att<4, false>(acc, a, x, 0, 16);
    tile_drain<4>(acc);
    MARK(12);
    T2DUMP(3);
    {
      release_prev<false>(x, true);
      mbar_wait(sb + B_STGFREE + wg * 8, 1);
      const uint32_t ad = sb + wg * 24576 + lane_off128(x);
      epi_hs<0>(acc, ad);
      epi_hs<1>(acc, ad + 8192);
      epi_hs<2>(acc, ad + 16384);
      fence_async_smem();
      mbar_arrive(sb + B_STAGED + wg * 96 + EV_T3 * 8);
    }
    x.gs = 5; x.gph = 0; x.lo = 2;
    pin_acc<0, 64>(acc);
    MARK(13);
    seg_att<2, true>(acc, a, x, 0, 16);
    tile_drain<2>(acc);
    MARK(14);
    T2DUMP(4);
    {
      release_prev<true>(x, true);
      mbar_wait(sb + B_STGFREE + wg * 8, 0);
      const uint32_t ad = sb + wg * 24576 + lane_off128(x);
      epi_hs<0>(acc, ad);
      epi_hs<1>(acc, ad + 8192);
      epi_hs<3>(acc, ad + 16384);
      fence_async_smem();
      mbar_arrive(sb + B_STAGED + wg * 96 + EV_T4 * 8);
    }
    pin_acc<0, 64>(acc);
    MARK(15);
    seg_att<2, true, true>(acc, a, x, 0, NATT_FINAL);
    {
    MARK(16);
    T2DUMP(5);
    seg_gemm<2, true>(acc, x, NATT_FINAL, 72);
    tile_drain<2>(acc);
    mbar_wait(full_bar<true>(x), x.gph);
    MARK(17);
    T2DUMP(6);
    {
      const uint32_t ad = slot_addr<true>(x) + wg * 8192 + lane_off128(x);
      epi_out<0>(acc, ad);
      epi_out<1>(acc, ad + 16384);
      staged<true>(x, EV_FIN);
    }
    }
    MARK(18);
  }
  asm volatile("barrier.cluster.arrive.release.aligned;\nbarrier.cluster.wait.acquire.aligned;" ::: "memory");
  MARK(19);
}

typedef CUresult (*EncodeFn)(CUtensorMap*, CUtensorMapDataType, cuuint32_t, void*, const cuuint64_t*, const cuuint64_t*, const cuuint32_t*,
                             const cuuint32_t*, CUtensorMapInterleave, CUtensorMapSwizzle, CUtensorMapL2promotion, CUtensorMapFloatOOBfill);
void make_map(EncodeFn enc, CUtensorMap* m, const void* ptr, uint64_t cols, uint64_t rows, uint32_t bc, uint32_t br, CUtensorMapSwizzle sw) {
  cuuint64_t dims[2] = {cols, rows}, strides[1] = {cols * 2};
  cuuint32_t box[2] = {bc, br}, es[2] = {1, 1};
  enc(m, CU_TENSOR_MAP_DATA_TYPE_BFLOAT16, 2, const_cast<void*>(ptr), dims, strides, box, es, CU_TENSOR_MAP_INTERLEAVE_NONE, sw,
      CU_TENSOR_MAP_L2_PROMOTION_L2_256B, CU_TENSOR_MAP_FLOAT_OOB_FILL_NONE);
}

}

extern "C" void kernel_launch(void* const* d_in, const int* in_sizes, int n_in, void* d_out, int out_size) {
  (void)in_sizes; (void)n_in; (void)out_size;
  void* fn = nullptr;
  cudaDriverEntryPointQueryResult qr;
  cudaGetDriverEntryPoint("cuTensorMapEncodeTiled", &fn, cudaEnableDefault, &qr);
  EncodeFn enc = (EncodeFn)fn;
  void* o_ptr = nullptr;
  cudaGetSymbolAddress(&o_ptr, g_o);
  Maps mp;
  make_map(enc, &mp.wqkv, d_in[1], 3072, 1024, 64, 32, CU_TENSOR_MAP_SWIZZLE_128B);
  make_map(enc, &mp.w1, d_in[4], 3584, 1024, 64, 32, CU_TENSOR_MAP_SWIZZLE_128B);
  make_map(enc, &mp.w2, d_in[5], 1024, 3584, 64, 64, CU_TENSOR_MAP_SWIZZLE_128B);
  make_map(enc, &mp.wo, d_in[2], 1024, 1024, 64, 64, CU_TENSOR_MAP_SWIZZLE_128B);
  make_map(enc, &mp.o_st, o_ptr, 1024, 2048, 32, 64, CU_TENSOR_MAP_SWIZZLE_64B);
  make_map(enc, &mp.o_ld, o_ptr, 1024, 2048, 64, 64, CU_TENSOR_MAP_SWIZZLE_128B);
  make_map(enc, &mp.x, d_in[0], 1024, 2048, 64, 64, CU_TENSOR_MAP_SWIZZLE_128B);
  make_map(enc, &mp.out, d_out, 1024, 2048, 64, 64, CU_TENSOR_MAP_SWIZZLE_128B);
  cudaFuncSetAttribute(fused_block_kernel, cudaFuncAttributeMaxDynamicSharedMemorySize, SMEM_BYTES);
  cudaLaunchConfig_t cfg = {};
  cfg.gridDim = dim3(NCTA);
  cfg.blockDim = dim3(384);
  cfg.dynamicSmemBytes = SMEM_BYTES;
  cfg.stream = cudaStreamPerThread;
  cudaLaunchAttribute at[1];
  at[0].id = cudaLaunchAttributeClusterDimension;
  at[0].val.clusterDim.x = 2; at[0].val.clusterDim.y = 1; at[0].val.clusterDim.z = 1;
  cfg.attrs = at; cfg.numAttrs = 1;
  cudaLaunchKernelEx(&cfg, fused_block_kernel, mp, (const __nv_bfloat16*)d_in[0]);
}
```

```cpp
#include <cuda_runtime.h>
#include <cuda_bf16.h>
#include <cuda.h>
#include <stdint.h>

namespace {


constexpr int SW = 24;
constexpr int XSLOT = (71 - SW) % 6;
constexpr int CHUNK = 1024, PACE = 150;
constexpr int NCTA = 128;
constexpr int D1 = 4;
constexpr int NATT_FINAL = 129 - (2 * (16 - D1) + 32 + 16);

constexpr uint32_t OFF_KV = 196608;
constexpr uint32_t OFF_QO = OFF_KV + 24576;
constexpr uint32_t OFF_BAR = OFF_QO + 8192;
constexpr uint32_t B_FULL48 = OFF_BAR, B_EMPTY48 = B_FULL48 + 32, B_FULL32 = B_EMPTY48 + 32, B_EMPTY32 = B_FULL32 + 48,
                   B_KVFULL = B_EMPTY32 + 48, B_KVEMPTY = B_KVFULL + 24, B_STAGED = B_KVEMPTY + 24,
                   B_OFREE = B_STAGED + 192,
                   B_LNRDY = B_OFREE + 24,
                   B_STGFREE = B_LNRDY + 8;
constexpr uint32_t B_XNDONE = B_STGFREE + 24, B_QFULL = B_OFREE + 16;
constexpr uint32_t OFF_SAFE = OFF_BAR + 480;
constexpr uint32_t OFF_NRM = OFF_BAR + 512;
constexpr uint32_t OFF_ONES = OFF_BAR + 1024;
constexpr uint32_t OFF_CS = OFF_ONES + 1024;
constexpr uint32_t SMEM_BYTES = OFF_CS + 1024;
enum { EV_T1, EV_T2, EV_T3, EV_T4, EV_FIN, EV_LN, EV_CS, EV_T1B, EV_O0 };

struct Sync {
  unsigned ln[16 * 8], st[16 * 8], cs[8 * 8];
  unsigned qkv[32 * 8];
  unsigned hA[16 * 8], hB[16 * 8], hC[16 * 8];
  unsigned oc[64 * 8];
  unsigned done[32];
};

__device__ __align__(1024) uint8_t g_xn[16 * 16 * 16384];
__device__ __align__(1024) uint8_t g_h[16 * 56 * 16384];
__device__ __align__(1024) uint8_t g_q[32 * 32 * 4096];
__device__ __align__(1024) uint8_t g_k[32 * 32 * 4096];
__device__ __align__(1024) uint8_t g_v[32 * 32 * 4096];
__device__ __align__(1024) __nv_bfloat16 g_o[2048 * 1024];
__device__ __align__(1024) uint32_t g_stat[2048];
__device__ __align__(1024) float g_csp[8 * 8 * 192];
__device__ __align__(1024) Sync g_sync;


__device__ __forceinline__ void mbar_init(uint32_t b, uint32_t c) { asm volatile("mbarrier.init.shared::cta.b64 [%0], %1;" ::"r"(b), "r"(c) : "memory"); }
__device__ __forceinline__ void mbar_expect(uint32_t b, uint32_t bytes) { asm volatile("mbarrier.arrive.expect_tx.shared::cta.b64 _, [%0], %1;" ::"r"(b), "r"(bytes) : "memory"); }
__device__ __forceinline__ void mbar_arrive(uint32_t b) { asm volatile("mbarrier.arrive.shared::cta.b64 _, [%0];" ::"r"(b) : "memory"); }
__device__ __forceinline__ void mbar_arrive_remote(uint32_t cluster_addr) {
  asm volatile("mbarrier.arrive.shared::cluster.b64 _, [%0];" ::"r"(cluster_addr) : "memory");
}
__device__ __forceinline__ uint32_t mapa(uint32_t a, uint32_t cta) {
  uint32_t r; asm("mapa.shared::cluster.u32 %0, %1, %2;" : "=r"(r) : "r"(a), "r"(cta)); return r;
}
__device__ __forceinline__ bool elect_one() {
  uint32_t r;
  asm volatile("{\n.reg .pred p;\nelect.sync _|p, 0xffffffff;\nselp.u32 %0, 1, 0, p;\n}" : "=r"(r));
  return r != 0;
}
__device__ __forceinline__ void mbar_wait(uint32_t b, uint32_t ph) {
  asm volatile("{\n.reg .pred p;\n.reg .u32 n;\n"
               "mbarrier.try_wait.parity.shared::cta.b64 p, [%0], %1;\n@p bra LAB_DONE;\nmov.u32 n, 0;\n"
               "LAB_WAIT:\nmbarrier.try_wait.parity.shared::cta.b64 p, [%0], %1;\n@p bra LAB_DONE;\n"
               "add.u32 n, n, 1;\nsetp.lt.u32 p, n, 1000000;\n@p bra LAB_WAIT;\ntrap;\nLAB_DONE:\n}" ::"r"(b), "r"(ph) : "memory");
}
__device__ __forceinline__ void mbar_wait_idle(uint32_t b, uint32_t ph) {
  asm volatile("{\n.reg .pred p;\n.reg .u32 n;\nmov.u32 n, 0;\n"
               "LAB_WAIT:\nmbarrier.test_wait.parity.shared::cta.b64 p, [%0], %1;\n@p bra LAB_DONE;\n"
               "nanosleep.u32 %2;\nadd.u32 n, n, 1;\nsetp.lt.u32 p, n, 1000000;\n@p bra LAB_WAIT;\ntrap;\nLAB_DONE:\n"
               "fence.proxy.async.shared::cta;\n}" ::"r"(b), "r"(ph), "n"(200) : "memory");
}
__device__ __forceinline__ uint32_t mbar_test(uint32_t b, uint32_t ph) {
  uint32_t ok;
  asm volatile("{\n.reg .pred p;\nmbarrier.test_wait.parity.shared::cta.b64 p, [%1], %2;\nselp.u32 %0, 1, 0, p;\n}" : "=r"(ok) : "r"(b), "r"(ph) : "memory");
  return ok;
}
__device__ __forceinline__ void poll_ge(const unsigned* p, unsigned target) {
  asm volatile("{\n.reg .pred p;\n.reg .u32 n, v;\nmov.u32 n, 0;\n"
               "LAB_POLL:\nld.acquire.gpu.global.u32 v, [%0];\nsetp.ge.u32 p, v, %1;\n@p bra LAB_DONE;\n"
               "nanosleep.u32 40;\nadd.u32 n, n, 1;\nsetp.lt.u32 p, n, 1000000;\n@p bra LAB_POLL;\ntrap;\nLAB_DONE:\n"
               "fence.proxy.async.global;\n}" ::"l"(p), "r"(target) : "memory");
}
__device__ __forceinline__ unsigned peek(const unsigned* p) {
  unsigned v;
  asm volatile("ld.relaxed.gpu.global.u32 %0, [%1];" : "=r"(v) : "l"(p) : "memory");
  return v;
}
__device__ __forceinline__ void confirm(const unsigned* p, unsigned seen, unsigned target) {
  if (seen < target) poll_ge(p, target);
  else asm volatile("fence.proxy.async.global;" ::: "memory");
}
__device__ __forceinline__ void publish() { asm volatile("fence.acq_rel.gpu;" ::: "memory"); }
__device__ __forceinline__ void bump(unsigned* p) { asm volatile("red.relaxed.gpu.global.add.u32 [%0], 1;" ::"l"(p) : "memory"); }
__device__ __forceinline__ void fence_async_smem() { asm volatile("fence.proxy.async.shared::cta;" ::: "memory"); }
__device__ __forceinline__ void tma2d(uint32_t dst, const CUtensorMap* m, int c0, int c1, uint32_t bar) {
  asm volatile("cp.async.bulk.tensor.2d.shared::cluster.global.mbarrier::complete_tx::bytes [%0], [%1, {%3, %4}], [%2];"
               ::"r"(dst), "l"(m), "r"(bar), "r"(c0), "r"(c1) : "memory");
}
__device__ __forceinline__ void tma2d_mc(uint32_t dst, const CUtensorMap* m, int c0, int c1, uint32_t bar) {
  asm volatile("cp.async.bulk.tensor.2d.shared::cluster.global.mbarrier::complete_tx::bytes.multicast::cluster [%0], [%1, {%3, %4}], [%2], %5;"
               ::"r"(dst), "l"(m), "r"(bar), "r"(c0), "r"(c1), "h"((uint16_t)3) : "memory");
}
__device__ __forceinline__ void bulk_ld(uint32_t dst, const void* src, uint32_t bytes, uint32_t bar) {
  asm volatile("cp.async.bulk.shared::cluster.global.mbarrier::complete_tx::bytes [%0], [%1], %2, [%3];" ::"r"(dst), "l"(src), "r"(bytes), "r"(bar) : "memory");
}
__device__ __forceinline__ void bulk_ld_mc(uint32_t dst, const void* src, uint32_t bytes, uint32_t bar) {
  asm volatile("cp.async.bulk.shared::cluster.global.mbarrier::complete_tx::bytes.multicast::cluster [%0], [%1], %2, [%3], %4;"
               ::"r"(dst), "l"(src), "r"(bytes), "r"(bar), "h"((uint16_t)3) : "memory");
}
__device__ __forceinline__ void bulk_st(void* dst, uint32_t src, uint32_t bytes) {
  asm volatile("cp.async.bulk.global.shared::cta.bulk_group [%0], [%1], %2;" ::"l"(dst), "r"(src), "r"(bytes) : "memory");
}
__device__ __forceinline__ void tma2d_st(const CUtensorMap* m, int c0, int c1, uint32_t src) {
  asm volatile("cp.async.bulk.tensor.2d.global.shared::cta.bulk_group [%0, {%2, %3}], [%1];" ::"l"(m), "r"(src), "r"(c0), "r"(c1) : "memory");
}
__device__ __forceinline__ void bulk_commit() { asm volatile("cp.async.bulk.commit_group;" ::: "memory"); }
template <int N> __device__ __forceinline__ void bulk_wait_read() { asm volatile("cp.async.bulk.wait_group.read %0;" ::"n"(N) : "memory"); }
template <int N> __device__ __forceinline__ void bulk_wait() { asm volatile("cp.async.bulk.wait_group %0;" ::"n"(N) : "memory"); }
__device__ __forceinline__ void wg_fence() { asm volatile("wgmma.fence.sync.aligned;" ::: "memory"); }
__device__ __forceinline__ void wg_commit() { asm volatile("wgmma.commit_group.sync.aligned;" ::: "memory"); }
template <int N> __device__ __forceinline__ void wg_wait() { asm volatile("wgmma.wait_group.sync.aligned %0;" ::"n"(N) : "memory"); }
__device__ __forceinline__ float ex2(float x) { float y; asm("ex2.approx.ftz.f32 %0, %1;" : "=f"(y) : "f"(x)); return y; }
__device__ __forceinline__ float rcp(float x) { float y; asm("rcp.approx.ftz.f32 %0, %1;" : "=f"(y) : "f"(x)); return y; }
__device__ __forceinline__ uint32_t pack2(float lo, float hi) { uint32_t r; asm("cvt.rn.bf16x2.f32 %0, %1, %2;" : "=r"(r) : "f"(hi), "f"(lo)); return r; }
__device__ __forceinline__ uint32_t pack2_relu(float lo, float hi) { uint32_t r; asm("cvt.rn.relu.bf16x2.f32 %0, %1, %2;" : "=r"(r) : "f"(hi), "f"(lo)); return r; }
__device__ __forceinline__ float bf_lo(uint32_t u) { return __uint_as_float(u << 16); }
__device__ __forceinline__ float bf_hi(uint32_t u) { return __uint_as_float(u & 0xffff0000u); }
__device__ __forceinline__ float bf_round(float x) { return __bfloat162float(__float2bfloat16_rn(x)); }
__device__ __forceinline__ void stsm4(uint32_t a, uint32_t r0, uint32_t r1, uint32_t r2, uint32_t r3) {
  asm volatile("stmatrix.sync.aligned.m8n8.x4.shared.b16 [%0], {%1, %2, %3, %4};" ::"r"(a), "r"(r0), "r"(r1), "r"(r2), "r"(r3) : "memory");
}
__device__ __forceinline__ void ldsm4(uint32_t a, uint32_t& r0, uint32_t& r1, uint32_t& r2, uint32_t& r3) {
  asm volatile("ldmatrix.sync.aligned.m8n8.x4.shared.b16 {%0, %1, %2, %3}, [%4];" : "=r"(r0), "=r"(r1), "=r"(r2), "=r"(r3) : "r"(a) : "memory");
}
__device__ __forceinline__ void sts128(uint32_t a, uint32_t r0, uint32_t r1, uint32_t r2, uint32_t r3) {
  asm volatile("st.shared.v4.b32 [%0], {%1, %2, %3, %4};" ::"r"(a), "r"(r0), "r"(r1), "r"(r2), "r"(r3) : "memory");
}
__device__ __forceinline__ void sts32(uint32_t a, uint32_t v) { asm volatile("st.shared.b32 [%0], %1;" ::"r"(a), "r"(v) : "memory"); }
__device__ __forceinline__ uint32_t lds32(uint32_t a) { uint32_t v; asm volatile("ld.shared.b32 %0, [%1];" : "=r"(v) : "r"(a) : "memory"); return v; }
template <int N> __device__ __forceinline__ void pin_f(float (&r)[N]) {
#pragma unroll
  for (int i = 0; i < N; i++) asm volatile("" : "+f"(r[i])::"memory");
}
template <int N> __device__ __forceinline__ void pin_u(uint32_t (&r)[N]) {
#pragma unroll
  for (int i = 0; i < N; i++) asm volatile("" : "+r"(r[i])::"memory");
}
template <int LO, int HI> __device__ __forceinline__ void pin_acc(float (&r)[128]) {
#pragma unroll
  for (int i = LO; i < HI; i++) asm volatile("" : "+f"(r[i])::"memory");
}

template <int LO, int HI> __device__ __forceinline__ void forget_acc(float (&r)[128]) {
#pragma unroll
  for (int i = LO; i < HI; i++) asm volatile("" : "=f"(r[i])::"memory");
}

__device__ __forceinline__ void mma_ss_n128(float (&d)[128], uint32_t alo, uint32_t blo, uint32_t sd) {
  asm volatile("{\n.reg .pred p;\n.reg .b64 da, db;\nsetp.ne.b32 p, %66, 0;\n"
    "mov.b64 da, {%64, 0x40000040};\nmov.b64 db, {%65, 0x40000040};\n"
    "wgmma.mma_async.sync.aligned.m64n128k16.f32.bf16.bf16 {%0, %1, %2, %3, %4, %5, %6, %7, %8, %9, %10, %11, %12, %13, %14, %15, %16, %17, %18, %19, %20, %21, %22, %23, %24, %25, %26, %27, %28, %29, %30, %31, %32, %33, %34, %35, %36, %37, %38, %39, %40, %41, %42, %43, %44, %45, %46, %47, %48, %49, %50, %51, %52, %53, %54, %55, %56, %57, %58, %59, %60, %61, %62, %63}, da, db, p, 1, 1, 0, 1;\n}\n"
    : "+f"(d[0]), "+f"(d[1]), "+f"(d[2]), "+f"(d[3]), "+f"(d[4]), "+f"(d[5]), "+f"(d[6]), "+f"(d[7]), "+f"(d[8]), "+f"(d[9]), "+f"(d[10]), "+f"(d[11]), "+f"(d[12]), "+f"(d[13]), "+f"(d[14]), "+f"(d[15]), "+f"(d[16]), "+f"(d[17]), "+f"(d[18]), "+f"(d[19]), "+f"(d[20]), "+f"(d[21]), "+f"(d[22]), "+f"(d[23]), "+f"(d[24]), "+f"(d[25]), "+f"(d[26]), "+f"(d[27]), "+f"(d[28]), "+f"(d[29]), "+f"(d[30]), "+f"(d[31]), "+f"(d[32]), "+f"(d[33]), "+f"(d[34]), "+f"(d[35]), "+f"(d[36]), "+f"(d[37]), "+f"(d[38]), "+f"(d[39]), "+f"(d[40]), "+f"(d[41]), "+f"(d[42]), "+f"(d[43]), "+f"(d[44]), "+f"(d[45]), "+f"(d[46]), "+f"(d[47]), "+f"(d[48]), "+f"(d[49]), "+f"(d[50]), "+f"(d[51]), "+f"(d[52]), "+f"(d[53]), "+f"(d[54]), "+f"(d[55]), "+f"(d[56]), "+f"(d[57]), "+f"(d[58]), "+f"(d[59]), "+f"(d[60]), "+f"(d[61]), "+f"(d[62]), "+f"(d[63])
    : "r"(alo), "r"(blo), "r"(sd));
}
__device__ __forceinline__ void mma_ss_n192(float (&d)[128], uint32_t alo, uint32_t blo, uint32_t sd) {
  asm volatile("{\n.reg .pred p;\n.reg .b64 da, db;\nsetp.ne.b32 p, %98, 0;\n"
    "mov.b64 da, {%96, 0x40000040};\nmov.b64 db, {%97, 0x40000040};\n"
    "wgmma.mma_async.sync.aligned.m64n192k16.f32.bf16.bf16 {%0, %1, %2, %3, %4, %5, %6, %7, %8, %9, %10, %11, %12, %13, %14, %15, %16, %17, %18, %19, %20, %21, %22, %23, %24, %25, %26, %27, %28, %29, %30, %31, %32, %33, %34, %35, %36, %37, %38, %39, %40, %41, %42, %43, %44, %45, %46, %47, %48, %49, %50, %51, %52, %53, %54, %55, %56, %57, %58, %59, %60, %61, %62, %63, %64, %65, %66, %67, %68, %69, %70, %71, %72, %73, %74, %75, %76, %77, %78, %79, %80, %81, %82, %83, %84, %85, %86, %87, %88, %89, %90, %91, %92, %93, %94, %95}, da, db, p, 1, 1, 0, 1;\n}\n"
    : "+f"(d[0]), "+f"(d[1]), "+f"(d[2]), "+f"(d[3]), "+f"(d[4]), "+f"(d[5]), "+f"(d[6]), "+f"(d[7]), "+f"(d[8]), "+f"(d[9]), "+f"(d[10]), "+f"(d[11]), "+f"(d[12]), "+f"(d[13]), "+f"(d[14]), "+f"(d[15]), "+f"(d[16]), "+f"(d[17]), "+f"(d[18]), "+f"(d[19]), "+f"(d[20]), "+f"(d[21]), "+f"(d[22]), "+f"(d[23]), "+f"(d[24]), "+f"(d[25]), "+f"(d[26]), "+f"(d[27]), "+f"(d[28]), "+f"(d[29]), "+f"(d[30]), "+f"(d[31]), "+f"(d[32]), "+f"(d[33]), "+f"(d[34]), "+f"(d[35]), "+f"(d[36]), "+f"(d[37]), "+f"(d[38]), "+f"(d[39]), "+f"(d[40]), "+f"(d[41]), "+f"(d[42]), "+f"(d[43]), "+f"(d[44]), "+f"(d[45]), "+f"(d[46]), "+f"(d[47]), "+f"(d[48]), "+f"(d[49]), "+f"(d[50]), "+f"(d[51]), "+f"(d[52]), "+f"(d[53]), "+f"(d[54]), "+f"(d[55]), "+f"(d[56]), "+f"(d[57]), "+f"(d[58]), "+f"(d[59]), "+f"(d[60]), "+f"(d[61]), "+f"(d[62]), "+f"(d[63]), "+f"(d[64]), "+f"(d[65]), "+f"(d[66]), "+f"(d[67]), "+f"(d[68]), "+f"(d[69]), "+f"(d[70]), "+f"(d[71]), "+f"(d[72]), "+f"(d[73]), "+f"(d[74]), "+f"(d[75]), "+f"(d[76]), "+f"(d[77]), "+f"(d[78]), "+f"(d[79]), "+f"(d[80]), "+f"(d[81]), "+f"(d[82]), "+f"(d[83]), "+f"(d[84]), "+f"(d[85]), "+f"(d[86]), "+f"(d[87]), "+f"(d[88]), "+f"(d[89]), "+f"(d[90]), "+f"(d[91]), "+f"(d[92]), "+f"(d[93]), "+f"(d[94]), "+f"(d[95])
    : "r"(alo), "r"(blo), "r"(sd));
}
__device__ __forceinline__ void mma_ss_n256(float (&d)[128], uint32_t alo, uint32_t blo, uint32_t sd) {
  asm volatile("{\n.reg .pred p;\n.reg .b64 da, db;\nsetp.ne.b32 p, %130, 0;\n"
    "mov.b64 da, {%128, 0x40000040};\nmov.b64 db, {%129, 0x40000040};\n"
    "wgmma.mma_async.sync.aligned.m64n256k16.f32.bf16.bf16 {%0, %1, %2, %3, %4, %5, %6, %7, %8, %9, %10, %11, %12, %13, %14, %15, %16, %17, %18, %19, %20, %21, %22, %23, %24, %25, %26, %27, %28, %29, %30, %31, %32, %33, %34, %35, %36, %37, %38, %39, %40, %41, %42, %43, %44, %45, %46, %47, %48, %49, %50, %51, %52, %53, %54, %55, %56, %57, %58, %59, %60, %61, %62, %63, %64, %65, %66, %67, %68, %69, %70, %71, %72, %73, %74, %75, %76, %77, %78, %79, %80, %81, %82, %83, %84, %85, %86, %87, %88, %89, %90, %91, %92, %93, %94, %95, %96, %97, %98, %99, %100, %101, %102, %103, %104, %105, %106, %107, %108, %109, %110, %111, %112, %113, %114, %115, %116, %117, %118, %119, %120, %121, %122, %123, %124, %125, %126, %127}, da, db, p, 1, 1, 0, 1;\n}\n"
    : "+f"(d[0]), "+f"(d[1]), "+f"(d[2]), "+f"(d[3]), "+f"(d[4]), "+f"(d[5]), "+f"(d[6]), "+f"(d[7]), "+f"(d[8]), "+f"(d[9]), "+f"(d[10]), "+f"(d[11]), "+f"(d[12]), "+f"(d[13]), "+f"(d[14]), "+f"(d[15]), "+f"(d[16]), "+f"(d[17]), "+f"(d[18]), "+f"(d[19]), "+f"(d[20]), "+f"(d[21]), "+f"(d[22]), "+f"(d[23]), "+f"(d[24]), "+f"(d[25]), "+f"(d[26]), "+f"(d[27]), "+f"(d[28]), "+f"(d[29]), "+f"(d[30]), "+f"(d[31]), "+f"(d[32]), "+f"(d[33]), "+f"(d[34]), "+f"(d[35]), "+f"(d[36]), "+f"(d[37]), "+f"(d[38]), "+f"(d[39]), "+f"(d[40]), "+f"(d[41]), "+f"(d[42]), "+f"(d[43]), "+f"(d[44]), "+f"(d[45]), "+f"(d[46]), "+f"(d[47]), "+f"(d[48]), "+f"(d[49]), "+f"(d[50]), "+f"(d[51]), "+f"(d[52]), "+f"(d[53]), "+f"(d[54]), "+f"(d[55]), "+f"(d[56]), "+f"(d[57]), "+f"(d[58]), "+f"(d[59]), "+f"(d[60]), "+f"(d[61]), "+f"(d[62]), "+f"(d[63]), "+f"(d[64]), "+f"(d[65]), "+f"(d[66]), "+f"(d[67]), "+f"(d[68]), "+f"(d[69]), "+f"(d[70]), "+f"(d[71]), "+f"(d[72]), "+f"(d[73]), "+f"(d[74]), "+f"(d[75]), "+f"(d[76]), "+f"(d[77]), "+f"(d[78]), "+f"(d[79]), "+f"(d[80]), "+f"(d[81]), "+f"(d[82]), "+f"(d[83]), "+f"(d[84]), "+f"(d[85]), "+f"(d[86]), "+f"(d[87]), "+f"(d[88]), "+f"(d[89]), "+f"(d[90]), "+f"(d[91]), "+f"(d[92]), "+f"(d[93]), "+f"(d[94]), "+f"(d[95]), "+f"(d[96]), "+f"(d[97]), "+f"(d[98]), "+f"(d[99]), "+f"(d[100]), "+f"(d[101]), "+f"(d[102]), "+f"(d[103]), "+f"(d[104]), "+f"(d[105]), "+f"(d[106]), "+f"(d[107]), "+f"(d[108]), "+f"(d[109]), "+f"(d[110]), "+f"(d[111]), "+f"(d[112]), "+f"(d[113]), "+f"(d[114]), "+f"(d[115]), "+f"(d[116]), "+f"(d[117]), "+f"(d[118]), "+f"(d[119]), "+f"(d[120]), "+f"(d[121]), "+f"(d[122]), "+f"(d[123]), "+f"(d[124]), "+f"(d[125]), "+f"(d[126]), "+f"(d[127])
    : "r"(alo), "r"(blo), "r"(sd));
}
__device__ __forceinline__ void mma_qk(float (&d)[32], uint32_t a0, uint32_t a1, uint32_t a2, uint32_t a3, uint32_t blo, uint32_t sd) {
  asm volatile("{\n.reg .pred p;\n.reg .b64 db;\nsetp.ne.b32 p, %37, 0;\nmov.b64 db, {%36, 0x80000020};\n"
    "wgmma.mma_async.sync.aligned.m64n64k16.f32.bf16.bf16 {%0, %1, %2, %3, %4, %5, %6, %7, %8, %9, %10, %11, %12, %13, %14, %15, %16, %17, %18, %19, %20, %21, %22, %23, %24, %25, %26, %27, %28, %29, %30, %31}, {%32, %33, %34, %35}, db, p, 1, 1, 0;\n}\n"
    : "+f"(d[0]), "+f"(d[1]), "+f"(d[2]), "+f"(d[3]), "+f"(d[4]), "+f"(d[5]), "+f"(d[6]), "+f"(d[7]), "+f"(d[8]), "+f"(d[9]), "+f"(d[10]), "+f"(d[11]), "+f"(d[12]), "+f"(d[13]), "+f"(d[14]), "+f"(d[15]), "+f"(d[16]), "+f"(d[17]), "+f"(d[18]), "+f"(d[19]), "+f"(d[20]), "+f"(d[21]), "+f"(d[22]), "+f"(d[23]), "+f"(d[24]), "+f"(d[25]), "+f"(d[26]), "+f"(d[27]), "+f"(d[28]), "+f"(d[29]), "+f"(d[30]), "+f"(d[31])
    : "r"(a0), "r"(a1), "r"(a2), "r"(a3), "r"(blo), "r"(sd));
}
__device__ __forceinline__ void mma_pv(float (&d)[20], uint32_t a0, uint32_t a1, uint32_t a2, uint32_t a3, uint32_t blo, uint32_t sd) {
  asm volatile("{\n.reg .pred p;\n.reg .b64 db;\nsetp.ne.b32 p, %25, 0;\nmov.b64 db, {%24, 0x80000020};\n"
    "wgmma.mma_async.sync.aligned.m64n40k16.f32.bf16.bf16 {%0, %1, %2, %3, %4, %5, %6, %7, %8, %9, %10, %11, %12, %13, %14, %15, %16, %17, %18, %19}, {%20, %21, %22, %23}, db, p, 1, 1, 1;\n}\n"
    : "+f"(d[0]), "+f"(d[1]), "+f"(d[2]), "+f"(d[3]), "+f"(d[4]), "+f"(d[5]), "+f"(d[6]), "+f"(d[7]), "+f"(d[8]), "+f"(d[9]), "+f"(d[10]), "+f"(d[11]), "+f"(d[12]), "+f"(d[13]), "+f"(d[14]), "+f"(d[15]), "+f"(d[16]), "+f"(d[17]), "+f"(d[18]), "+f"(d[19])
    : "r"(a0), "r"(a1), "r"(a2), "r"(a3), "r"(blo), "r"(sd));
}
__device__ __forceinline__ void mma_cs(float (&d)[32], uint32_t a0, uint32_t a1, uint32_t a2, uint32_t a3, uint32_t blo, uint32_t sd) {
  asm volatile("{\n.reg .pred p;\n.reg .b64 db;\nsetp.ne.b32 p, %37, 0;\nmov.b64 db, {%36, 0x40000040};\n"
    "wgmma.mma_async.sync.aligned.m64n64k16.f32.bf16.bf16 {%0, %1, %2, %3, %4, %5, %6, %7, %8, %9, %10, %11, %12, %13, %14, %15, %16, %17, %18, %19, %20, %21, %22, %23, %24, %25, %26, %27, %28, %29, %30, %31}, {%32, %33, %34, %35}, db, p, 1, 1, 1;\n}\n"
    : "+f"(d[0]), "+f"(d[1]), "+f"(d[2]), "+f"(d[3]), "+f"(d[4]), "+f"(d[5]), "+f"(d[6]), "+f"(d[7]), "+f"(d[8]), "+f"(d[9]), "+f"(d[10]), "+f"(d[11]), "+f"(d[12]), "+f"(d[13]), "+f"(d[14]), "+f"(d[15]), "+f"(d[16]), "+f"(d[17]), "+f"(d[18]), "+f"(d[19]), "+f"(d[20]), "+f"(d[21]), "+f"(d[22]), "+f"(d[23]), "+f"(d[24]), "+f"(d[25]), "+f"(d[26]), "+f"(d[27]), "+f"(d[28]), "+f"(d[29]), "+f"(d[30]), "+f"(d[31])
    : "r"(a0), "r"(a1), "r"(a2), "r"(a3), "r"(blo), "r"(sd));
}

template <int NP> __device__ __forceinline__ void mma_g(float (&d)[128], uint32_t a, uint32_t b, uint32_t sd) {
  if constexpr (NP == 2) mma_ss_n128(d, a, b, sd);
  else if constexpr (NP == 3) mma_ss_n192(d, a, b, sd);
  else mma_ss_n256(d, a, b, sd);
}

struct Att {
  float S[32];
  uint32_t P[16];
  float O[20];
  uint32_t Q[8];
  float m0, m1;
  uint32_t j;
  uint32_t kvs;
  uint32_t kvph;
  uint32_t relk;
  uint32_t kd, vd;
  uint32_t safe;
};
struct Ctx {
  uint32_t sb;
  uint32_t wg;
  uint32_t t;
  uint32_t gs;
  uint32_t gph;
  uint32_t lo;
  uint32_t rb;
  uint32_t relg;
  uint32_t da, db;
  uint32_t qo;
};

template <bool P32> __device__ __forceinline__ void ring_next(Ctx& x) {
  if (++x.gs == (P32 ? 6u : 4u)) { x.gs = x.lo; x.gph ^= 1; }
}
template <bool P32> __device__ __forceinline__ uint32_t slot_addr(const Ctx& x) { return x.sb + x.gs * (P32 ? 32768u : 49152u); }
template <bool P32> __device__ __forceinline__ uint32_t full_bar(const Ctx& x) { return x.sb + (P32 ? B_FULL32 : B_FULL48) + x.gs * 8; }
template <bool P32> __device__ __forceinline__ void release_prev(const Ctx& x, bool on) {
  const uint32_t ps = x.gs == x.lo ? (P32 ? 5u : 3u) : x.gs - 1;
  if (x.t < 2 && on) mbar_arrive_remote(x.rb + (P32 ? B_EMPTY32 : B_EMPTY48) + ps * 8);
}
template <bool P32> __device__ __forceinline__ uint32_t desc_a(const Ctx& x) { return (((slot_addr<P32>(x) & 0x3FFFFu) + x.wg * 8192) >> 4) + (1u << 16); }
template <bool P32> __device__ __forceinline__ uint32_t desc_b(const Ctx& x) { return (((slot_addr<P32>(x) & 0x3FFFFu) + 16384) >> 4) + (512u << 16); }
__device__ __forceinline__ uint32_t lane_off64(const Ctx& x) {
  const uint32_t lane = x.t & 31;
  return ((x.t >> 5) * 16 + (lane & 7) + (lane & 8)) * 64 + (((lane >> 4) ^ ((lane & 7) >> 1)) << 4);
}
__device__ __forceinline__ uint32_t lane_off128(const Ctx& x) {
  const uint32_t lane = x.t & 31;
  return ((x.t >> 5) * 16 + (lane & 7) + (lane & 8)) * 128 + (((lane >> 4) ^ (lane & 7)) << 4);
}

constexpr uint32_t VSTEP = 64u - (64u << 16);
__device__ __forceinline__ void kv_desc(Att& a, const Ctx& x) {
  const uint32_t k16 = (((x.sb & 0x3FFFFu) + OFF_KV) >> 4) + a.kvs * 64;
  a.kd = k16 + (1u << 16);
  a.vd = k16 + 256 + ((((OFF_ONES - OFF_KV - 4096) >> 4) - a.kvs * 64) << 16);
}
__device__ __forceinline__ void load_q(Att& a, const Ctx& x) {
  ldsm4(x.qo, a.Q[0], a.Q[1], a.Q[2], a.Q[3]);
  ldsm4(x.qo ^ 32, a.Q[4], a.Q[5], a.Q[6], a.Q[7]);
}

template <int NP, int G0, int GN, bool P32>
__device__ __forceinline__ void att_step(float (&acc)[128], Att& a, Ctx& x, bool first_kb) {
  const uint32_t jm = a.j & 31;
  uint32_t ok = mbar_test(x.sb + B_KVFULL + a.kvs, a.kvph);
  if constexpr (G0 == 0) ok &= mbar_test(full_bar<P32>(x), x.gph);
#pragma unroll
  for (int i = 0; i < 16; i++) a.P[i] = pack2(a.S[2 * i], a.S[2 * i + 1]);
  pin_u(a.P);
  if (__builtin_expect(!ok || jm == 0, 0)) {
    if (!ok) {
      mbar_wait(x.sb + B_KVFULL + a.kvs, a.kvph);
      if constexpr (G0 == 0) mbar_wait(full_bar<P32>(x), x.gph);
    }
    if (jm == 0) {
      mbar_wait(x.sb + B_QFULL, (min(a.j, 96u) >> 5) & 1);
      load_q(a, x);
    }
  }
  pin_u(a.Q);
  wg_fence();
  mma_pv(a.O, a.P[0], a.P[1], a.P[2], a.P[3], a.vd, jm != 1);
  mma_pv(a.O, a.P[4], a.P[5], a.P[6], a.P[7], a.vd + VSTEP, 1);
  mma_pv(a.O, a.P[8], a.P[9], a.P[10], a.P[11], a.vd + 2 * VSTEP, 1);
  mma_pv(a.O, a.P[12], a.P[13], a.P[14], a.P[15], a.vd + 3 * VSTEP, 1);
  mma_qk(a.S, a.Q[0], a.Q[1], a.Q[2], a.Q[3], a.kd, 0);
  mma_qk(a.S, a.Q[4], a.Q[5], a.Q[6], a.Q[7], a.kd + 2, 1);
  wg_commit();
#pragma unroll
  for (int g = G0; g < G0 + GN; g++) mma_g<NP>(acc, x.da + 2 * g, x.db + 128 * g, g == 0 ? (uint32_t)!first_kb : 1u);
  wg_commit();
  wg_wait<1>();
  pin_f(a.S); pin_f(a.O); pin_u(a.P); pin_u(a.Q);
  if (x.t < 2) mbar_arrive_remote(a.relk);
  if constexpr (G0 == 0) { if (x.t < 2 && !first_kb) mbar_arrive_remote(x.relg); }
  const bool rare = jm == 0 || a.safe;
  if (__builtin_expect(rare, 0)) {
    if (jm == 0) {
      if (a.j != 0) {
        const float l0 = rcp(a.O[16]), l1 = rcp(a.O[18]);
        const uint32_t ad = x.qo;
        stsm4(ad, pack2(a.O[0] * l0, a.O[1] * l0), pack2(a.O[2] * l1, a.O[3] * l1), pack2(a.O[4] * l0, a.O[5] * l0), pack2(a.O[6] * l1, a.O[7] * l1));
        stsm4(ad ^ 32, pack2(a.O[8] * l0, a.O[9] * l0), pack2(a.O[10] * l1, a.O[11] * l1), pack2(a.O[12] * l0, a.O[13] * l0), pack2(a.O[14] * l1, a.O[15] * l1));
        mbar_arrive(x.sb + B_STAGED + x.wg * 96 + (EV_O0 - 1 + (a.j >> 5)) * 8);
      }
      a.m0 = -INFINITY; a.m1 = -INFINITY;
      a.safe = lds32(x.sb + OFF_SAFE + ((a.j >> 5) & 3) * 4);
    }
    if (a.safe) {
      float x0 = a.m0, x1 = a.m1;
#pragma unroll
      for (int i = 0; i < 8; i++) { x0 = fmaxf(x0, fmaxf(a.S[4 * i], a.S[4 * i + 1])); x1 = fmaxf(x1, fmaxf(a.S[4 * i + 2], a.S[4 * i + 3])); }
      x0 = fmaxf(x0, __shfl_xor_sync(0xffffffffu, x0, 1)); x1 = fmaxf(x1, __shfl_xor_sync(0xffffffffu, x1, 1));
      x0 = fmaxf(x0, __shfl_xor_sync(0xffffffffu, x0, 2)); x1 = fmaxf(x1, __shfl_xor_sync(0xffffffffu, x1, 2));
      const float s0 = ex2(a.m0 - x0), s1 = ex2(a.m1 - x1);
      a.m0 = x0; a.m1 = x1;
#pragma unroll
      for (int i = 0; i < 5; i++) { a.O[4 * i] *= s0; a.O[4 * i + 1] *= s0; a.O[4 * i + 2] *= s1; a.O[4 * i + 3] *= s1; }
#pragma unroll
      for (int i = 0; i < 8; i++) { a.S[4 * i] -= x0; a.S[4 * i + 1] -= x0; a.S[4 * i + 2] -= x1; a.S[4 * i + 3] -= x1; }
    }
  }
  pin_f(a.S); pin_f(a.O);
  a.kvs += 8;
  if (a.kvs == 24) { a.kvs = 0; a.kvph ^= 1; }
  kv_desc(a, x);
  a.relk = x.rb + B_KVEMPTY + a.kvs;
  if constexpr (G0 + GN == 4) {
    x.relg = x.rb + (P32 ? B_EMPTY32 : B_EMPTY48) + x.gs * 8;
    ring_next<P32>(x);
    x.da = desc_a<P32>(x); x.db = desc_b<P32>(x);
  }
  asm volatile("" : "+r"(a.kd), "+r"(a.vd), "+r"(x.da), "+r"(x.db), "+r"(a.relk), "+r"(x.relg)::"memory");
#pragma unroll
  for (int i = 0; i < 32; i++) a.S[i] = ex2(a.S[i]);
  pin_f(a.S);
  a.j++;
}

template <int NP, bool P32>
__device__ __forceinline__ void seg_gemm(float (&acc)[128], Ctx& x, int kb0, int kb1) {
#pragma unroll 1
  for (int kb = kb0; kb < kb1; kb++) {
    mbar_wait(full_bar<P32>(x), x.gph);
    const uint32_t da = desc_a<P32>(x), db = desc_b<P32>(x);
    wg_fence();
#pragma unroll
    for (int g = 0; g < 4; g++) mma_g<NP>(acc, da + 2 * g, db + 128 * g, g == 0 ? (uint32_t)(kb != 0) : 1u);
    wg_commit();
    wg_wait<1>();
    release_prev<P32>(x, kb != 0 && kb < 68);
    ring_next<P32>(x);
  }
}
template <int NP, bool P32, bool FINAL = false>
__device__ __forceinline__ void seg_att(float (&acc)[128], Att& a, Ctx& x, int kb0, int kb1) {
  x.da = desc_a<P32>(x); x.db = desc_b<P32>(x);
  x.relg = x.rb + (P32 ? B_EMPTY32 : B_EMPTY48) + (x.gs == x.lo ? (P32 ? 5u : 3u) : x.gs - 1) * 8;
#pragma unroll 1
  for (int kb = kb0; kb < kb1; kb++) {
    if constexpr (NP == 4) {
      att_step<NP, 0, 2, P32>(acc, a, x, kb == 0);
      att_step<NP, 2, 2, P32>(acc, a, x, false);
    } else {
      if constexpr (FINAL) x.lo = kb < SW - 2 ? 2 : 0;
      att_step<NP, 0, 4, P32>(acc, a, x, kb == 0);
    }
  }
}
template <int NP> __device__ __forceinline__ void tile_drain(float (&acc)[128]) {
  wg_wait<0>();
  pin_acc<0, NP * 32>(acc);
}
template <bool P32> __device__ __forceinline__ uint32_t transit_buf(const Ctx& x) {
  return x.sb + (x.gs == x.lo ? (P32 ? 5u : 3u) : x.gs - 1) * (P32 ? 32768u : 49152u) + x.wg * 8192;
}

__device__ __forceinline__ uint32_t hfma2(uint32_t a, uint32_t b, uint32_t c) { uint32_t d; asm("fma.rn.bf16x2 %0, %1, %2, %3;" : "=r"(d) : "r"(a), "r"(b), "r"(c)); return d; }
__device__ __forceinline__ uint32_t hadd2(uint32_t a, uint32_t b) { uint32_t d; asm("add.rn.bf16x2 %0, %1, %2;" : "=r"(d) : "r"(a), "r"(b)); return d; }
__device__ __forceinline__ uint32_t norm_max(const uint32_t (&r)[8]) {
  const uint32_t a = hfma2(r[6], r[6], hfma2(r[4], r[4], hfma2(r[2], r[2], hfma2(r[0], r[0], 0u))));
  const uint32_t b = hfma2(r[7], r[7], hfma2(r[5], r[5], hfma2(r[3], r[3], hfma2(r[1], r[1], 0u))));
  uint32_t t = hadd2(__byte_perm(a, b, 0x5410), __byte_perm(a, b, 0x7632));
  t = hadd2(t, __shfl_xor_sync(0xffffffffu, t, 1));
  t = hadd2(t, __shfl_xor_sync(0xffffffffu, t, 2));
  return __reduce_max_sync(0xffffffffu, max(t & 0xffff0000u, t << 16));
}
constexpr float QSCALE = 0.17677669529663687f * 1.4426950408889634f;
template <bool SCALE_Q, int H0, int H1> __device__ __forceinline__ void epi_qkv(const float (&acc)[128], const Ctx& x, uint32_t stg) {
  const uint32_t lane = x.t & 31, nd = x.sb + OFF_NRM + x.wg * 128 + (x.t >> 5) * 32;
  const uint32_t ad = stg + lane_off64(x);
  uint32_t r[6][8];
#pragma unroll
  for (int u = 0; u < 6; u++) {
    if ((u & 1) < H0 || (u & 1) >= H1) continue;
#pragma unroll
    for (int i = 0; i < 8; i++) {
      const int o = u * 16 + i * 2;
      r[u][i] = (u < 2 && SCALE_Q) ? pack2(acc[o] * QSCALE, acc[o + 1] * QSCALE) : pack2(acc[o], acc[o + 1]);
    }
    pin_u(r[u]);
  }
#pragma unroll
  for (int u = 0; u < 6; u++) {
    if ((u & 1) < H0 || (u & 1) >= H1) continue;
    stsm4(ad + u * 4096, r[u][0], r[u][1], r[u][2], r[u][3]);
    stsm4((ad ^ 32) + u * 4096, r[u][4], r[u][5], r[u][6], r[u][7]);
  }
#pragma unroll
  for (int h = H0; h < H1; h++) {
    const uint32_t m0 = norm_max(r[h]), m1 = norm_max(r[2 + h]), m2 = norm_max(r[4 + h]);
    if (lane == 0) sts128(nd + h * 16, m0, m1, m2, 0u);
  }
}
template <int PN> __device__ __forceinline__ void epi_hs(const float (&acc)[128], uint32_t ad) {
#pragma unroll
  for (int b = 0; b < 8; b += 2) {
    const int o = PN * 32 + b * 4;
    stsm4(ad ^ (b << 4), pack2_relu(acc[o], acc[o + 1]), pack2_relu(acc[o + 2], acc[o + 3]), pack2_relu(acc[o + 4], acc[o + 5]), pack2_relu(acc[o + 6], acc[o + 7]));
  }
}
__device__ __forceinline__ void epi_out(const float (&acc)[128], uint32_t ad) {
  uint32_t r[32];
#pragma unroll
  for (int u = 0; u < 8; u++) ldsm4((ad ^ ((u & 3) << 5)) + (u >> 2) * 16384, r[4 * u], r[4 * u + 1], r[4 * u + 2], r[4 * u + 3]);
#pragma unroll
  for (int h = 0; h < 2; h++) {
#pragma unroll
    for (int i = 16 * h; i < 16 * h + 16; i++) r[i] = pack2(acc[2 * i] + bf_lo(r[i]), acc[2 * i + 1] + bf_hi(r[i]));
#pragma unroll
    for (int u = 4 * h; u < 4 * h + 4; u++) stsm4((ad ^ ((u & 3) << 5)) + h * 16384, r[4 * u], r[4 * u + 1], r[4 * u + 2], r[4 * u + 3]);
  }
}

__device__ __forceinline__ float3 row_sums(const uint4 (&v)[4]) {
  const float z = __shfl_sync(0xffffffffu, bf_lo(v[0].x), 0);
  float s0 = 0.f, s1 = 0.f, q0 = 0.f, q1 = 0.f;
#pragma unroll
  for (int i = 0; i < 4; i++) {
    const uint32_t u[4] = {v[i].x, v[i].y, v[i].z, v[i].w};
#pragma unroll
    for (int k = 0; k < 4; k++) { const float d0 = bf_lo(u[k]) - z, d1 = bf_hi(u[k]) - z; s0 += d0; s1 += d1; q0 += d0 * d0; q1 += d1 * d1; }
  }
  return make_float3(s0 + s1, q0 + q1, z);
}
__device__ __forceinline__ void row_stats(float3 (&t)[2], float2 (&st)[2], uint32_t (&packed)[2]) {
#pragma unroll
  for (int o = 16; o; o >>= 1) {
#pragma unroll
    for (int r = 0; r < 2; r++) { t[r].x += __shfl_xor_sync(0xffffffffu, t[r].x, o); t[r].y += __shfl_xor_sync(0xffffffffu, t[r].y, o); }
  }
#pragma unroll
  for (int r = 0; r < 2; r++) {
    const float m = t[r].x * (1.f / 1024.f), var = fmaxf(t[r].y * (1.f / 1024.f) - m * m, 0.f);
    float sd;
    asm("sqrt.approx.f32 %0, %1;" : "=f"(sd) : "f"(bf_round(bf_round(var) + 1e-5f)));
    packed[r] = pack2(m + t[r].z, sd);
    st[r] = make_float2(bf_lo(packed[r]), rcp(bf_hi(packed[r])));
  }
}
__device__ __forceinline__ void row_stage(const uint4 (&v)[4], float2 st, uint32_t stg, uint32_t r, uint32_t lane) {
#pragma unroll
  for (int i = 0; i < 4; i++) {
    const uint32_t ci = lane + 32 * i;
    sts128(stg + (ci >> 3) * 2048 + r * 128 + (((ci & 7) ^ (r & 7)) << 4),
           pack2((bf_lo(v[i].x) - st.x) * st.y, (bf_hi(v[i].x) - st.x) * st.y), pack2((bf_lo(v[i].y) - st.x) * st.y, (bf_hi(v[i].y) - st.x) * st.y),
           pack2((bf_lo(v[i].z) - st.x) * st.y, (bf_hi(v[i].z) - st.x) * st.y), pack2((bf_lo(v[i].w) - st.x) * st.y, (bf_hi(v[i].w) - st.x) * st.y));
  }
}

__device__ __forceinline__ uint4 head_peek(uint32_t head) {
  uint4 e;
  asm volatile("ld.relaxed.gpu.global.v4.u32 {%0, %1, %2, %3}, [%4];" : "=r"(e.x), "=r"(e.y), "=r"(e.z), "=r"(e.w) : "l"(&g_sync.qkv[head * 8]) : "memory");
  return e;
}
__device__ __forceinline__ uint32_t head_ready(uint32_t head, uint4 e) {
  for (uint32_t n = 0; e.x < 32; n++) {
    if (n > 1000000) __trap();
    __nanosleep(40);
    e = head_peek(head);
  }
  asm volatile("fence.proxy.async.global;" ::: "memory");
  const float fq = __uint_as_float(e.y), fk = __uint_as_float(e.z), fv = __uint_as_float(e.w);
  const bool ok = (fq * fk <= 7700.f) && (fq <= 1e18f) && (fk <= 1e18f) && (fv <= 1e14f) && (fv >= 1e-10f);
  return ok ? 0u : 1u;
}
__device__ __forceinline__ void head_norms(uint32_t nrm, uint32_t head, uint32_t lane) {
  uint32_t v = lds32(nrm + (lane & 3) * 32 + (head & 1) * 16 + min(lane >> 2, 2u) * 4);
  v = max(v, __shfl_xor_sync(0xffffffffu, v, 1));
  v = max(v, __shfl_xor_sync(0xffffffffu, v, 2));
  if (lane < 12 && (lane & 3) == 0) asm volatile("red.relaxed.gpu.global.max.u32 [%0], %1;" ::"l"(&g_sync.qkv[head * 8 + 1 + (lane >> 2)]), "r"(v) : "memory");
  __syncwarp();
}

__device__ __forceinline__ uint32_t stat_off(uint32_t w) { return w == 0 ? OFF_NRM + 256 : OFF_CS + 768; }
__device__ __forceinline__ void ln_gather(uint32_t sb, uint32_t c, uint32_t mt, uint32_t w, uint32_t lane) {
  const float4* src = reinterpret_cast<const float4*>(g_csp + (c * 8 + (lane >> 3) * 2) * 192 + w * 96) + (lane & 7);
  float4 e[6];
#pragma unroll
  for (int i = 0; i < 6; i++) e[i] = __ldcg(src + (i & 1) * 48 + (i >> 1) * 8);
  const uint2 st = __ldcg(reinterpret_cast<const uint2*>(g_stat + mt * 128 + w * 64) + lane);
#pragma unroll
  for (int i = 0; i < 3; i++) {
    float t[4] = {e[2 * i].x + e[2 * i + 1].x, e[2 * i].y + e[2 * i + 1].y, e[2 * i].z + e[2 * i + 1].z, e[2 * i].w + e[2 * i + 1].w};
#pragma unroll
    for (int k = 0; k < 4; k++) { t[k] += __shfl_xor_sync(0xffffffffu, t[k], 8); t[k] += __shfl_xor_sync(0xffffffffu, t[k], 16); }
    if (lane < 8) sts128(sb + OFF_CS + w * 384 + i * 128 + lane * 16, __float_as_uint(t[0]), __float_as_uint(t[1]), __float_as_uint(t[2]), __float_as_uint(t[3]));
  }
  asm volatile("st.shared.v2.b32 [%0], {%1, %2};" ::"r"(sb + stat_off(w) + lane * 8), "r"(st.x), "r"(st.y) : "memory");
  __syncwarp();
  if (lane == 0) mbar_arrive(sb + B_LNRDY);
}

__device__ __forceinline__ uint32_t item_head(uint32_t item, uint32_t c) { return item < 2 ? 2 * c + item : item * 8 + c; }

struct Maps { CUtensorMap wqkv, w1, w2, wo, o_st, o_ld, x, out; };

__global__ void __launch_bounds__(384, 1) fused_block_kernel(const __grid_constant__ Maps mp, const __nv_bfloat16* __restrict__ xin) {
  extern __shared__ __align__(1024) uint8_t smem[];
  const uint32_t sb = (uint32_t)__cvta_generic_to_shared(smem);
  const uint32_t tid = threadIdx.x;
  const uint32_t wg = __shfl_sync(0xffffffffu, tid >> 7, 0);
  uint32_t rank;
  asm("mov.u32 %0, %%cluster_ctarank;" : "=r"(rank));
  const uint32_t cid = blockIdx.x >> 1, p = cid >> 3, c = cid & 7, mt = 2 * p + rank;
  const uint32_t fm = cid >> 2, fn = (cid & 3) * 2 + rank;
  if (tid == 256) {
    if (sb & 1023) __trap();
    mbar_init(sb + B_FULL48, 1);
    fence_async_smem();
    {
      const int kb = p == 0 ? 6 : 0;
      mbar_expect(sb + B_FULL48, 40960);
      tma2d(sb, &mp.x, kb * 64, mt * 128, sb + B_FULL48);
      tma2d(sb + 8192, &mp.x, kb * 64, mt * 128 + 64, sb + B_FULL48);
#pragma unroll
      for (int u = 0; u < 6; u++) tma2d(sb + 16384 + u * 4096, &mp.wqkv, c * 64 + (u >> 1) * 1024, kb * 64 + (u & 1) * 32, sb + B_FULL48);
    }
#pragma unroll
    for (int i = 0; i < 4; i++) { if (i) mbar_init(sb + B_FULL48 + 8 * i, 1); mbar_init(sb + B_EMPTY48 + 8 * i, 4); }
#pragma unroll
    for (int i = 0; i < 3; i++) { mbar_init(sb + B_KVFULL + 8 * i, 1); mbar_init(sb + B_KVEMPTY + 8 * i, 4); }
  } else if (tid == 288) {
#pragma unroll
    for (int i = 0; i < 6; i++) { mbar_init(sb + B_FULL32 + 8 * i, 1); mbar_init(sb + B_EMPTY32 + 8 * i, 4); }
#pragma unroll
    for (int i = 0; i < 5; i++) {
      mbar_arrive(sb + B_FULL32 + 8 * i);
      asm volatile("mbarrier.arrive.shared::cta.b64 _, [%0], 4;" ::"r"(sb + B_EMPTY32 + 8 * i) : "memory");
    }
  } else if (tid == 320) {
#pragma unroll
    for (int i = 0; i <= EV_O0 + 3; i++) mbar_init(sb + B_STAGED + 8 * i, 128);
    mbar_init(sb + B_OFREE, 2); mbar_init(sb + B_OFREE + 8, 2); mbar_init(sb + B_QFULL, 1); mbar_init(sb + B_LNRDY, 2); mbar_init(sb + B_XNDONE, 2);
  } else if (tid == 352) {
#pragma unroll
    for (int i = 0; i <= EV_O0 + 3; i++) mbar_init(sb + B_STAGED + 96 + 8 * i, 128);
    mbar_init(sb + B_STGFREE, 1); mbar_init(sb + B_STGFREE + 8, 1); mbar_init(sb + B_STGFREE + 16, 4);
  }
  asm volatile("fence.mbarrier_init.release.cluster;" ::: "memory");
  __syncwarp();
  asm volatile("barrier.cluster.arrive.relaxed.aligned;" ::: "memory");

  if (wg == 2) {
    asm volatile("setmaxnreg.dec.sync.aligned.u32 40;");
    asm volatile("barrier.cluster.wait.acquire.aligned;" ::: "memory");
    const uint32_t warp = __shfl_sync(0xffffffffu, (tid >> 5) & 3, 0);
    if (warp == 2) {
      uint32_t s = 1, ph = 1;
      const uint8_t* xa = g_xn + mt * 16 * 16384;
      const uint32_t boff = 16384 + rank * 4096;
      uint32_t lo = 0;
      auto next48 = [&]() { if (++s == 4) { s = lo; ph ^= 1; } };
      auto next32 = [&]() { if (++s == 6) { s = lo; ph ^= 1; } };
#pragma unroll 1
      for (int i = 1; i < 16; i++) {
        const int kb = (i >> 1) == 3 ? 2 * p + (i & 1) : (i >> 1) == (int)p ? 6 + (i & 1) : i;
        const uint32_t dst = sb + s * 49152, fb = sb + B_FULL48 + s * 8;
        mbar_wait(sb + B_EMPTY48 + s * 8, ph);
        if (elect_one()) {
          mbar_expect(fb, 40960);
          tma2d(dst, &mp.x, kb * 64, mt * 128, fb);
          tma2d(dst + 8192, &mp.x, kb * 64, mt * 128 + 64, fb);
#pragma unroll
          for (int u = 0; u < 3; u++) tma2d_mc(dst + boff + u * 8192, &mp.wqkv, c * 64 + u * 1024, kb * 64 + rank * 32, fb);
        }
        next48();
      }
      poll_ge(&g_sync.ln[mt * 8], 8);
      s = 1; lo = 1;
#pragma unroll 1
      for (int kb = 0; kb < 16; kb++) {
        const uint32_t dst = sb + s * 49152, fb = sb + B_FULL48 + s * 8;
        mbar_wait(sb + B_EMPTY48 + s * 8, ph);
        if (elect_one()) {
          mbar_expect(fb, 49152);
          bulk_ld(dst, xa + kb * 16384, 16384, fb);
#pragma unroll
          for (int i = 0; i < 3; i++) tma2d_mc(dst + boff + i * 8192, &mp.wqkv, (8 + c) * 64 + i * 1024, kb * 64 + rank * 32, fb);
          tma2d_mc(dst + boff + 24576, &mp.w1, c * 64, kb * 64 + rank * 32, fb);
        }
        next48();
      }
#pragma unroll 1
      for (int kb = 0; kb < 16; kb++) {
        const uint32_t dst = sb + s * 49152, fb = sb + B_FULL48 + s * 8;
        mbar_wait(sb + B_EMPTY48 + s * 8, ph);
        if (elect_one()) {
          mbar_expect(fb, 49152);
          bulk_ld(dst, xa + kb * 16384, 16384, fb);
#pragma unroll
          for (int i = 0; i < 4; i++) tma2d_mc(dst + boff + i * 8192, &mp.w1, (i < 3 ? 8 + 3 * c + i : 32 + c) * 64, kb * 64 + rank * 32, fb);
        }
        next48();
      }
      s = 5; ph = 1; lo = 2;
      unsigned seen = 0;
#pragma unroll 1
      for (int kb = 0; kb < 16; kb++) {
        const uint32_t dst = sb + s * 32768, fb = sb + B_FULL32 + s * 8;
        if (kb == 0) mbar_wait(sb + B_EMPTY48 + 24, 1);
        if (kb == 1 || kb == 2) mbar_wait(sb + B_EMPTY48 + kb * 8, 0);
        mbar_wait(sb + B_EMPTY32 + s * 8, ph);
        if (elect_one()) {
          mbar_expect(fb, 32768);
          bulk_ld(dst, xa + kb * 16384, 16384, fb);
          tma2d_mc(dst + boff, &mp.w1, (40 + 2 * c) * 64, kb * 64 + rank * 32, fb);
          tma2d_mc(dst + boff + 8192, &mp.w1, (41 + 2 * c) * 64, kb * 64 + rank * 32, fb);
        }
        if (kb == 14) seen = peek(&g_sync.hA[fm * 8]);
        next32();
      }
      const uint8_t* ha = g_h + fm * 56 * 16384 + rank * 8192;
#pragma unroll 1
      for (int part = 0; part < 4; part++) {
        constexpr int PS = SW < 32 ? 2 : 3, PC = 5 - PS, K2 = SW < 32 ? SW + 1 : 32, K3 = SW < 32 ? 32 : SW + 1;
        auto counter = [&](int i) {
          return i == 0 ? &g_sync.hA[fm * 8] : i == 1 ? &g_sync.hB[fm * 8] : i == PC ? &g_sync.hC[fm * 8] : &g_sync.oc[(fm * 4 + (i == PS)) * 8];
        };
        const unsigned* nxt = counter(part + 1);
        if (part == PS) mbar_wait(sb + B_STGFREE + 16, 0);
        mbar_wait(sb + B_EMPTY32 + s * 8, ph);
        confirm(counter(part), seen, 16);
        const int kb1 = part == 0 ? 8 : part == 1 ? K2 : part == 2 ? K3 : 56;
#pragma unroll 1
        for (int kb = part == 0 ? 0 : part == 1 ? 8 : part == 2 ? K2 : K3; kb < kb1; kb++) {
          const uint32_t dst = sb + s * 32768, fb = sb + B_FULL32 + s * 8;
          mbar_wait(sb + B_EMPTY32 + s * 8, ph);
          if (elect_one()) {
            mbar_expect(fb, 32768);
            bulk_ld_mc(dst + rank * 8192, ha + kb * 16384, 8192, fb);
            tma2d(dst + 16384, &mp.w2, fn * 128, kb * 64, fb);
            tma2d(dst + 24576, &mp.w2, fn * 128 + 64, kb * 64, fb);
          }
          if (kb == kb1 - 2) seen = peek(nxt);
          if (kb == SW - 2) lo = 0;
          next32();
        }
      }
#pragma unroll 1
      for (int r = 0; r < 4; r++) {
        mbar_wait(sb + B_EMPTY32 + s * 8, ph);
        if (r != 1) confirm(&g_sync.oc[(fm * 4 + r) * 8], seen, 16);
#pragma unroll 1
        for (int kb = r * 4; kb < r * 4 + 4; kb++) {
          const uint32_t dst = sb + s * 32768, fb = sb + B_FULL32 + s * 8;
          mbar_wait(sb + B_EMPTY32 + s * 8, ph);
          if (elect_one()) {
            mbar_expect(fb, 32768);
            tma2d_mc(dst + rank * 8192, &mp.o_ld, kb * 64, fm * 128 + rank * 64, fb);
            tma2d(dst + 16384, &mp.wo, fn * 128, kb * 64, fb);
            tma2d(dst + 24576, &mp.wo, fn * 128 + 64, kb * 64, fb);
          }
          if (kb == 6 || kb == 11) seen = peek(&g_sync.oc[(fm * 4 + (kb == 6 ? 2 : 3)) * 8]);
          next32();
        }
      }
      mbar_wait(sb + B_EMPTY32 + s * 8, ph);
      if (elect_one()) {
        const uint32_t fb = sb + B_FULL32 + s * 8;
        mbar_expect(fb, 32768);
#pragma unroll
        for (int i = 0; i < 4; i++) tma2d(sb + s * 32768 + i * 8192, &mp.x, fn * 128 + (i >> 1) * 64, fm * 128 + (i & 1) * 64, fb);
      }
      unsigned ticket = 0;
      if ((tid & 31) == 0) ticket = atomicAdd(&g_sync.done[0], 1u);
      if (__shfl_sync(0xffffffffu, ticket, 0) == NCTA - 1) {
        uint4* z = reinterpret_cast<uint4*>(&g_sync);
        for (uint32_t i = tid & 31; i < sizeof(Sync) / 16; i += 32) z[i] = make_uint4(0, 0, 0, 0);
      }
    } else if (warp == 3) {
      uint32_t s = 0, ph = 1;
      const uint8_t* const kvb = rank == 0 ? g_k : g_v;
      const uint8_t* src = kvb + 2 * c * 32 * 4096;
      const uint32_t dst = sb + OFF_KV + rank * 4096;
      mbar_wait(sb + B_STAGED + EV_LN * 8, 0);
      mbar_wait(sb + B_STAGED + 96 + EV_LN * 8, 0);
      fence_async_smem();
#pragma unroll 1
      for (int kb = 0; kb < 16; kb++) {
        if (elect_one()) bulk_st(g_xn + (mt * 16 + kb) * 16384 + c * 2048, sb + OFF_KV + kb * 2048, 2048);
        __nanosleep(60);
      }
      if (elect_one()) {
        bulk_commit();
        bulk_wait<0>();
        publish();
        bump(&g_sync.ln[mt * 8]);
        mbar_arrive_remote(mapa(sb + B_XNDONE, 0));
        mbar_arrive_remote(mapa(sb + B_XNDONE, 1));
      }
      mbar_wait(sb + B_XNDONE, 0);
      sts32(sb + OFF_SAFE, head_ready(2 * c, head_peek(2 * c)));
      auto stage = [&](bool adv) {
        mbar_wait(sb + B_KVEMPTY + s * 8, ph);
        if (elect_one()) {
          mbar_expect(sb + B_KVFULL + s * 8, 8192);
          bulk_ld_mc(dst + s * 8192, src, 4096, sb + B_KVFULL + s * 8);
        }
        if (adv) src += 4096;
        if (++s == 3) { s = 0; ph ^= 1; }
      };
#pragma unroll 1
      for (int item = 0; item < 4; item++) {
        if (item == 0) {
          if (elect_one()) {
            mbar_expect(sb + B_KVFULL, 4096);
            bulk_ld(sb + OFF_KV, g_k + 2 * c * 32 * 4096, 4096, sb + B_KVFULL);
            mbar_expect(sb + B_QFULL, 8192);
            bulk_ld(sb + OFF_QO, g_q + (2 * c * 32 + mt * 2) * 4096, 8192, sb + B_QFULL);
          }
          if (rank == 0) src += 4096;
          s = 1;
        } else {
          stage(true);
        }
        if (rank == 1 && item != 0) src = kvb + item_head(item, c) * 32 * 4096;
#pragma unroll 1
        for (int j = 1; j < 22; j++) stage(true);
        {
          const uint32_t nx = min(item + 1, 3);
          const uint4 seen = head_peek(item_head(nx, c));
          stage(true);
          stage(true);
          sts32(sb + OFF_SAFE + nx * 4, head_ready(item_head(nx, c), seen));
        }
        if (item < 3) {
          if (item >= 1) mbar_wait(sb + B_OFREE + (item - 1) * 8, 0);
          if (elect_one()) {
            mbar_expect(sb + B_QFULL, 8192);
            bulk_ld(sb + OFF_QO, g_q + (item_head(item + 1, c) * 32 + mt * 2) * 4096, 8192, sb + B_QFULL);
          }
        }
#pragma unroll 1
        for (int j = 24; j < 32; j++) stage(true);
        if (rank == 0) src = item == 3 ? src - 4096 : kvb + item_head(item + 1, c) * 32 * 4096;
      }
      stage(false);
    } else {
      const uint32_t w = warp, st = sb + B_STAGED + w * 96, rt = mt * 2 + w;
      uint8_t* hb = g_h + mt * 56 * 16384 + w * 8192;
      const bool lead = elect_one();
      const uint32_t rb0 = mapa(sb, 0), rb1 = mapa(sb, 1);
      auto release = [&](uint32_t bar) { if (lead) { mbar_arrive_remote(rb0 + bar); mbar_arrive_remote(rb1 + bar); } };
      auto copy_out = [&](uint8_t* dst, uint32_t src, int bytes) {
#pragma unroll 1
        for (int o = 0; o < bytes; o += CHUNK) {
          if (lead) bulk_st(dst + o, src + o, CHUNK);
          __nanosleep(PACE);
        }
      };
      auto copy_done = [&]() { if (lead) { bulk_commit(); bulk_wait<0>(); } };
      auto o_event = [&](uint32_t r) {
        if (r == 3) { __nanosleep(12000); mbar_wait(st + (EV_O0 + r) * 8, 0); fence_async_smem(); }
        else mbar_wait_idle(st + (EV_O0 + r) * 8, 0);
        if (lead) {
          tma2d_st(&mp.o_st, item_head(r, c) * 32, rt * 64, sb + OFF_QO + w * 4096);
          bulk_commit();
          bulk_wait<0>();
          if (r < 2) mbar_arrive(sb + B_OFREE + r * 8);
          publish();
          bump(&g_sync.oc[(mt * 4 + r) * 8]);
        }
      };
      sts128(sb + OFF_ONES + w * 512 + (tid & 31) * 16, 0x3f803f80u, 0x3f803f80u, 0x3f803f80u, 0x3f803f80u);
      fence_async_smem();
      mbar_wait(st + EV_CS * 8, 0);
      fence_async_smem();
      if (lead) {
        if (rank * 2 + w < 3) bulk_st(g_csp + (c * 8 + p) * 192 + (rank * 2 + w) * 64, sb + 40960 + w * 512, 256);
        bulk_st(g_stat + mt * 128 + c * 16 + w * 8, sb + 40960 + w * 512 + 256, 32);
        bulk_commit();
        bulk_wait<0>();
        publish();
        bump(&g_sync.cs[c * 8]);
        bump(&g_sync.st[mt * 8]);
      }
      __syncwarp();
      {
        const unsigned seen = peek(&g_sync.st[mt * 8]);
        poll_ge(&g_sync.cs[c * 8], 32);
        if (seen < 16) poll_ge(&g_sync.st[mt * 8], 16);
      }
      ln_gather(sb, c, mt, w, tid & 31);
      mbar_wait(st + EV_T1 * 8, 0);
      fence_async_smem();
      head_norms(sb + OFF_NRM + w * 128, 2 * c, tid & 31);
      if (lead) {
        bulk_st(g_k + (2 * c * 32 + rt) * 4096, sb + w * 24576 + 8192, 4096);
        bulk_st(g_q + (2 * c * 32 + rt) * 4096, sb + w * 24576, 4096);
        bulk_st(g_v + (2 * c * 32 + rt) * 4096, sb + w * 24576 + 16384, 4096);
        bulk_commit();
        bulk_wait<0>();
        publish();
        bump(&g_sync.qkv[2 * c * 8]);
      }
      __nanosleep(1500);
      mbar_wait_idle(st + EV_T1B * 8, 0);
      head_norms(sb + OFF_NRM + w * 128, 2 * c + 1, tid & 31);
#pragma unroll 1
      for (int i = 0; i < 3; i++)
        copy_out((i == 0 ? g_q : i == 1 ? g_k : g_v) + ((2 * c + 1) * 32 + rt) * 4096, sb + w * 24576 + i * 8192 + 4096, 4096);
      copy_done();
      if (lead) { mbar_arrive(sb + B_STGFREE + w * 8); publish(); bump(&g_sync.qkv[(2 * c + 1) * 8]); }
      mbar_wait_idle(st + EV_T2 * 8, 0);
      if (lead) {
        bulk_st(hb + c * 16384, sb + 49152 + w * 8192, 8192);
        bulk_commit();
        bulk_wait<0>();
      }
      release(B_EMPTY48 + 8);
      head_norms(sb + OFF_NRM + w * 128, 16 + 2 * c, tid & 31);
      head_norms(sb + OFF_NRM + w * 128, 17 + 2 * c, tid & 31);
#pragma unroll 1
      for (int i = 0; i < 6; i++)
        copy_out((i < 2 ? g_q : i < 4 ? g_k : g_v) + ((16 + 2 * c + (i & 1)) * 32 + rt) * 4096, sb + w * 24576 + i * 4096, 4096);
      copy_done();
      if (lead) { mbar_arrive(sb + B_STGFREE + w * 8); publish(); bump(&g_sync.qkv[(16 + 2 * c) * 8]); bump(&g_sync.qkv[(17 + 2 * c) * 8]); bump(&g_sync.hA[mt * 8]); }
      o_event(0);
      mbar_wait_idle(st + EV_T3 * 8, 0);
#pragma unroll 1
      for (int i = 0; i < 3; i++) copy_out(hb + (8 + 3 * c + i) * 16384, sb + w * 24576 + i * 8192, 8192);
      copy_done();
      if (lead) { mbar_arrive(sb + B_STGFREE + w * 8); publish(); bump(&g_sync.hB[mt * 8]); }
      o_event(1);
      mbar_wait_idle(st + EV_T4 * 8, 0);
#pragma unroll 1
      for (int i = 0; i < 3; i++) copy_out(hb + (i < 2 ? 40 + 2 * c + i : 32 + c) * 16384, sb + w * 24576 + i * 8192, 8192);
      copy_done();
      release(B_STGFREE + 16);
      if (lead) { publish(); bump(&g_sync.hC[mt * 8]); }
      o_event(2);
      o_event(3);
      mbar_wait(st + EV_FIN * 8, 0);
      fence_async_smem();
      if (lead) {
        tma2d_st(&mp.out, fn * 128, fm * 128 + w * 64, sb + XSLOT * 32768 + w * 8192);
        tma2d_st(&mp.out, fn * 128 + 64, fm * 128 + w * 64, sb + XSLOT * 32768 + w * 8192 + 16384);
        bulk_commit();
        bulk_wait<0>();
      }
    }
    __syncwarp();
  } else {
    asm volatile("setmaxnreg.inc.sync.aligned.u32 232;");
    asm volatile("barrier.cluster.wait.acquire.aligned;" ::: "memory");

    Ctx x{sb, wg, tid & 127, 0, 0, 0, mapa(sb, tid & 1), 0, 0, 0, 0};
    float acc[128];
    Att a;
    forget_acc<0, 96>(acc);

    {
      uint4 xv[2][4];
      const uint4* xr = reinterpret_cast<const uint4*>(xin + (size_t)(mt * 128 + c * 16 + (tid >> 5) * 2) * 1024) + (tid & 31);
      auto pin_x = [&]() {
#pragma unroll
        for (int i = 0; i < 8; i++) asm volatile("" : "+r"(xv[i >> 2][i & 3].x), "+r"(xv[i >> 2][i & 3].y), "+r"(xv[i >> 2][i & 3].z), "+r"(xv[i >> 2][i & 3].w));
      };
#pragma unroll
      for (int i = 0; i < 4; i++) {
        seg_gemm<3, false>(acc, x, i == 0 ? 0 : 2 + i - 1, 2 + i);
        xv[0][(i + 1) & 3] = __ldg(xr + 32 * ((i + 1) & 3));
        xv[1][(i + 1) & 3] = __ldg(xr + 128 + 32 * ((i + 1) & 3));
      }
      seg_gemm<3, false>(acc, x, 2 + 3, 6);
      float cs[32];
#pragma unroll
      for (int i = 0; i < 32; i++) cs[i] = 0.f;
      uint32_t one[4] = {0x3f803f80u, 0x3f803f80u, 0x3f803f80u, 0x3f803f80u};
      pin_f(cs);
      pin_u(one);
      const uint32_t pn = min(rank * 2 + wg, 2u);
      float2 rs[2];
      float3 sums[2];
#pragma unroll
      for (int kb = 0; kb < 2; kb++) {
        mbar_wait(full_bar<false>(x), x.gph);
        const uint32_t da = desc_a<false>(x), db = desc_b<false>(x);
        wg_fence();
#pragma unroll
        for (int g = 0; g < 4; g++) mma_cs(cs, one[0], one[1], one[2], one[3], db + pn * 512 + 128 * g, 1);
#pragma unroll
        for (int g = 0; g < 4; g++) mma_ss_n192(acc, da + 2 * g, db + 128 * g, 1);
        wg_commit();
        wg_wait<1>();
        release_prev<false>(x, true);
        ring_next<false>(x);
        sums[kb] = row_sums(xv[kb]);
        asm volatile("" : "+f"(sums[kb].x), "+f"(sums[kb].y));
        pin_x();
      }
      seg_gemm<3, false>(acc, x, 8, 9);
      uint32_t packed[2];
      row_stats(sums, rs, packed);
      pin_f(cs);
      const uint32_t small = sb + 40960 + wg * 512;
      if (x.t < 4) {
#pragma unroll
        for (int b = 0; b < 8; b++)
          asm volatile("st.shared.v2.f32 [%0], {%1, %2};" ::"r"(small + b * 32 + x.t * 8), "f"(cs[4 * b]), "f"(cs[4 * b + 1]) : "memory");
      }
      if ((tid & 31) == 0) asm volatile("st.shared.v2.b32 [%0], {%1, %2};" ::"r"(small + 256 + (x.t >> 5) * 8), "r"(packed[0]), "r"(packed[1]) : "memory");
      mbar_arrive(sb + B_STAGED + wg * 96 + EV_CS * 8);
      seg_gemm<3, false>(acc, x, 9, 10);
      row_stage(xv[0], rs[0], sb + OFF_KV, (tid >> 5) * 2, tid & 31);
      seg_gemm<3, false>(acc, x, 10, 11);
      row_stage(xv[1], rs[1], sb + OFF_KV, (tid >> 5) * 2 + 1, tid & 31);
      mbar_arrive(sb + B_STAGED + wg * 96 + EV_LN * 8);
    }
    seg_gemm<3, false>(acc, x, 11, 14);
    if (wg == 1) asm volatile("bar.sync 2, 256;" ::: "memory");
    seg_gemm<3, false>(acc, x, 14, 16);
    if (wg == 0) asm volatile("bar.arrive 2, 256;" ::: "memory");
    mbar_wait(sb + B_LNRDY, 0);
    const uint32_t sa = sb + stat_off(wg) + ((x.t >> 5) * 16 + ((x.t & 31) >> 2)) * 4, u0 = lds32(sa), u1 = lds32(sa + 32);
    const float2 st0 = make_float2(bf_lo(u0), rcp(bf_hi(u0))), st1 = make_float2(bf_lo(u1), rcp(bf_hi(u1)));
    const float q0 = st0.y * QSCALE, q1 = st1.y * QSCALE;
    tile_drain<3>(acc);
    release_prev<false>(x, true);
    mbar_wait(sb + B_EMPTY48, 1);
#pragma unroll
    for (int h = 0; h < 2; h++) {
#pragma unroll
      for (int b = 0; b < 24; b++) {
        if (((b >> 2) & 1) != h) continue;
        float2 cv;
        asm volatile("ld.shared.v2.f32 {%0, %1}, [%2];" : "=f"(cv.x), "=f"(cv.y) : "r"(sb + OFF_CS + b * 32 + (x.t & 3) * 8));
        const float s0 = b < 8 ? q0 : st0.y, s1 = b < 8 ? q1 : st1.y;
        acc[4 * b] = (acc[4 * b] - st0.x * cv.x) * s0; acc[4 * b + 1] = (acc[4 * b + 1] - st0.x * cv.y) * s0;
        acc[4 * b + 2] = (acc[4 * b + 2] - st1.x * cv.x) * s1; acc[4 * b + 3] = (acc[4 * b + 3] - st1.x * cv.y) * s1;
      }
      if (h == 0) epi_qkv<false, 0, 1>(acc, x, sb + wg * 24576); else epi_qkv<false, 1, 2>(acc, x, sb + wg * 24576);
      mbar_arrive(sb + B_STAGED + wg * 96 + (h == 0 ? EV_T1 : EV_T1B) * 8);
    }
    x.gs = 1; x.lo = 1;
#pragma unroll
    for (int i = 0; i < 32; i++) a.S[i] = 0.f;
#pragma unroll
    for (int i = 0; i < 8; i++) a.Q[i] = 0u;
#pragma unroll
    for (int i = 0; i < 20; i++) a.O[i] = 0.f;
    a.m0 = a.m1 = 0.f;
    a.j = 0; a.kvs = 0; a.kvph = 0; a.safe = 0;
    kv_desc(a, x);
    x.qo = sb + OFF_QO + wg * 4096 + lane_off64(x);
    asm volatile("" : "+r"(x.qo));
    a.relk = x.rb + B_KVEMPTY;
    forget_acc<0, 128>(acc); pin_f(a.S); pin_f(a.O); pin_u(a.Q);
    seg_gemm<4, false>(acc, x, 0, D1);
    seg_att<4, false>(acc, a, x, D1, 16);
    tile_drain<4>(acc);
    mbar_wait(sb + B_STGFREE + wg * 8, 0);
    epi_hs<3>(acc, transit_buf<false>(x) + lane_off128(x));
    epi_qkv<true, 0, 2>(acc, x, sb + wg * 24576);
    mbar_arrive(sb + B_STAGED + wg * 96 + EV_T2 * 8);
    forget_acc<0, 128>(acc);
    seg_att<4, false>(acc, a, x, 0, 16);
    tile_drain<4>(acc);
    {
      release_prev<false>(x, true);
      mbar_wait(sb + B_STGFREE + wg * 8, 1);
      const uint32_t ad = sb + wg * 24576 + lane_off128(x);
      epi_hs<0>(acc, ad);
      epi_hs<1>(acc, ad + 8192);
      epi_hs<2>(acc, ad + 16384);
      mbar_arrive(sb + B_STAGED + wg * 96 + EV_T3 * 8);
    }
    x.gs = 5; x.gph = 0; x.lo = 2;
    forget_acc<0, 64>(acc);
    seg_att<2, true>(acc, a, x, 0, 16);
    tile_drain<2>(acc);
    {
      release_prev<true>(x, true);
      mbar_wait(sb + B_STGFREE + wg * 8, 0);
      const uint32_t ad = sb + wg * 24576 + lane_off128(x);
      epi_hs<0>(acc, ad);
      epi_hs<1>(acc, ad + 8192);
      epi_hs<3>(acc, ad + 16384);
      mbar_arrive(sb + B_STAGED + wg * 96 + EV_T4 * 8);
    }
    forget_acc<0, 64>(acc);
    seg_att<2, true, true>(acc, a, x, 0, NATT_FINAL);
    {
    seg_gemm<2, true>(acc, x, NATT_FINAL, 72);
    tile_drain<2>(acc);
    mbar_wait(full_bar<true>(x), x.gph);
    {
      const uint32_t ad = slot_addr<true>(x) + wg * 8192 + lane_off128(x);
      epi_out(acc, ad);
      mbar_arrive(sb + B_STAGED + wg * 96 + EV_FIN * 8);
    }
    }
  }
  asm volatile("barrier.cluster.arrive.relaxed.aligned;\nbarrier.cluster.wait.aligned;" ::: "memory");
}

typedef CUresult (*EncodeFn)(CUtensorMap*, CUtensorMapDataType, cuuint32_t, void*, const cuuint64_t*, const cuuint64_t*, const cuuint32_t*,
                             const cuuint32_t*, CUtensorMapInterleave, CUtensorMapSwizzle, CUtensorMapL2promotion, CUtensorMapFloatOOBfill);
void make_map(EncodeFn enc, CUtensorMap* m, const void* ptr, uint64_t cols, uint64_t rows, uint32_t bc, uint32_t br, CUtensorMapSwizzle sw) {
  cuuint64_t dims[2] = {cols, rows}, strides[1] = {cols * 2};
  cuuint32_t box[2] = {bc, br}, es[2] = {1, 1};
  enc(m, CU_TENSOR_MAP_DATA_TYPE_BFLOAT16, 2, const_cast<void*>(ptr), dims, strides, box, es, CU_TENSOR_MAP_INTERLEAVE_NONE, sw,
      CU_TENSOR_MAP_L2_PROMOTION_L2_256B, CU_TENSOR_MAP_FLOAT_OOB_FILL_NONE);
}

}

extern "C" void kernel_launch(void* const* d_in, const int* in_sizes, int n_in, void* d_out, int out_size) {
  (void)in_sizes; (void)n_in; (void)out_size;
  void* fn = nullptr;
  cudaDriverEntryPointQueryResult qr;
  cudaGetDriverEntryPoint("cuTensorMapEncodeTiled", &fn, cudaEnableDefault, &qr);
  EncodeFn enc = (EncodeFn)fn;
  void* o_ptr = nullptr;
  cudaGetSymbolAddress(&o_ptr, g_o);
  Maps mp;
  make_map(enc, &mp.wqkv, d_in[1], 3072, 1024, 64, 32, CU_TENSOR_MAP_SWIZZLE_128B);
  make_map(enc, &mp.w1, d_in[4], 3584, 1024, 64, 32, CU_TENSOR_MAP_SWIZZLE_128B);
  make_map(enc, &mp.w2, d_in[5], 1024, 3584, 64, 64, CU_TENSOR_MAP_SWIZZLE_128B);
  make_map(enc, &mp.wo, d_in[2], 1024, 1024, 64, 64, CU_TENSOR_MAP_SWIZZLE_128B);
  make_map(enc, &mp.o_st, o_ptr, 1024, 2048, 32, 64, CU_TENSOR_MAP_SWIZZLE_64B);
  make_map(enc, &mp.o_ld, o_ptr, 1024, 2048, 64, 64, CU_TENSOR_MAP_SWIZZLE_128B);
  make_map(enc, &mp.x, d_in[0], 1024, 2048, 64, 64, CU_TENSOR_MAP_SWIZZLE_128B);
  make_map(enc, &mp.out, d_out, 1024, 2048, 64, 64, CU_TENSOR_MAP_SWIZZLE_128B);
  cudaFuncSetAttribute(fused_block_kernel, cudaFuncAttributeMaxDynamicSharedMemorySize, SMEM_BYTES);
  cudaLaunchConfig_t cfg = {};
  cfg.gridDim = dim3(NCTA);
  cfg.blockDim = dim3(384);
  cfg.dynamicSmemBytes = SMEM_BYTES;
  cfg.stream = cudaStreamPerThread;
  cudaLaunchAttribute at[1];
  at[0].id = cudaLaunchAttributeClusterDimension;
  at[0].val.clusterDim.x = 2; at[0].val.clusterDim.y = 1; at[0].val.clusterDim.z = 1;
  cfg.attrs = at; cfg.numAttrs = 1;
  cudaLaunchKernelEx(&cfg, fused_block_kernel, mp, (const __nv_bfloat16*)d_in[0]);
}
```
